```python
import torch

def _softmax(x, axis=-1):
    return torch.softmax(x, dim=axis)
def _gelu(x):
    return torch.nn.functional.gelu(x, approximate="tanh")
def _silu(x):
    return torch.nn.functional.silu(x)
def _sigmoid(x):
    return torch.sigmoid(x)
def _layernorm(x, axis=-1, eps=1e-5):
    m = x.mean(dim=axis, keepdim=True)
    v = x.var(dim=axis, keepdim=True, unbiased=False)
    return (x - m) / torch.sqrt(v + eps)
def _scatter_add(tgt, idx, src, axis=0):
    return tgt.clone().index_add_(axis, idx, src)
def _segment_sum(src, seg, n):
    out = torch.zeros((n,) + src.shape[1:], dtype=src.dtype)
    return out.index_add_(0, seg, src)
def _pad(x, pw):
    flat = tuple(v for pair in reversed(pw) for v in pair)
    return torch.nn.functional.pad(x, flat)

kernel_name = 'gated_mix__ssm_conv_s4d__glu_gated_bilinear__prompt'

def setup_inputs():

    _w = (lambda a: (lambda t: t.to(torch.bfloat16) if t.is_floating_point() else t)(torch.as_tensor(a)))
    def _A_setup():
        Bsz, L, D, N = 1, 2048, 512, 128
        return {
            "u": _w((lambda *s: torch.randn(*s, dtype=torch.bfloat16) * 0.05)(Bsz, L, D)),
            "log_A_real": _w((lambda *s: torch.randn(*s, dtype=torch.bfloat16) * 3.2)(D, N) * 0.5),
            "A_imag": _w((lambda *s: torch.randn(*s, dtype=torch.bfloat16) * 0.05)(D, N) * 3.14),
            "C_real": _w((lambda *s: torch.randn(*s, dtype=torch.bfloat16) * 0.05)(D, N) / N ** 0.5),
            "C_imag": _w((lambda *s: torch.randn(*s, dtype=torch.bfloat16) * 0.1)(D, N) / N ** 0.5),
            "log_dt": _w((lambda *s: torch.randn(*s, dtype=torch.bfloat16) * 0.05)(D) * 0.5 - 4.0),
            "D_skip": _w((lambda *s: torch.randn(*s, dtype=torch.bfloat16) * 0.05)(D)),
        }
    _A_in = _A_setup()

    def _B_setup():
        B, S, D, F = 1, 2048, 512, 1792
        return {
            "x": _w((lambda *s: torch.randn(*s, dtype=torch.bfloat16) * 0.05)(B, S, D)),
            "w_gate": _w((lambda *s: torch.randn(*s, dtype=torch.bfloat16) * 0.8)(D, F) * (D ** -0.5)),
            "w_up": _w((lambda *s: torch.randn(*s, dtype=torch.bfloat16) * 0.8)(D, F) * (D ** -0.5)),
            "w_down": _w((lambda *s: torch.randn(*s, dtype=torch.bfloat16) * 0.8)(F, D) * (F ** -0.5)),
        }
    _B_in = _B_setup()

    return {
        "A_u": _A_in["u"],
        "A_log_A_real": _A_in["log_A_real"],
        "A_A_imag": _A_in["A_imag"],
        "A_C_real": _A_in["C_real"],
        "A_C_imag": _A_in["C_imag"],
        "A_log_dt": _A_in["log_dt"],
        "A_D_skip": _A_in["D_skip"],
        "B_x": _B_in["x"],
        "B_w_gate": _B_in["w_gate"],
        "B_w_up": _B_in["w_up"],
        "B_w_down": _B_in["w_down"],
        "gate_w": _w((lambda *s: torch.randn(*s, dtype=torch.bfloat16) * 0.05)(512) * 16.0),
    }

def reference(A_u, A_log_A_real, A_A_imag, A_C_real, A_C_imag, A_log_dt, A_D_skip, B_x, B_w_gate, B_w_up, B_w_down, gate_w):
    def _A_ref(u, log_A_real, A_imag, C_real, C_imag, log_dt, D_skip):
        L = u.shape[1]
        dt = torch.exp(log_dt)
        A = -torch.exp(log_A_real) + 1j * A_imag
        C = (C_real + 1j * C_imag) * dt[:, None]
        pos = (lambda x, dt: x.to(dt))(torch.arange(L), log_dt.dtype)
        P = torch.exp((A * dt[:, None])[:, :, None] * pos[None, None, :])
        K = 2.0 * torch.einsum("dn,dnl->dl", C, P).real
        L2 = 2 * L
        u_t = (lambda x, *d: x.permute(*d))(u, 0, 2, 1)
        Kf = (lambda x, *a, **k: torch.fft.rfft(x.float(), *a, **k))(K, L2)
        Uf = (lambda x, *a, **k: torch.fft.rfft(x.float(), *a, **k))(u_t, L2)
        y = (lambda x, *a, **k: torch.fft.irfft(x, *a, **k).to(torch.bfloat16))(Uf * Kf[None, :, :], L2)[:, :, :L]
        y = (lambda x, *d: x.permute(*d))(y, 0, 2, 1)
        return y + u * D_skip[None, None, :]

    def _B_ref(x, w_gate, w_up, w_down):
        g = torch.einsum("bsd,df->bsf", x, w_gate)
        u = torch.einsum("bsd,df->bsf", x, w_up)
        h = g * u
        return torch.einsum("bsf,fd->bsd", h, w_down)

    x = A_u
    g = _sigmoid((x * gate_w).sum(-1, keepdims=True))
    a = _A_ref(x, A_log_A_real, A_A_imag, A_C_real, A_C_imag, A_log_dt, A_D_skip)
    b = _B_ref(x, B_w_gate, B_w_up, B_w_down)
    return g * a + (1 - g) * b
```

```cpp
#include <cuda_runtime.h>
#include <cuda_bf16.h>
#include <cuda.h>
#include <stdint.h>

namespace {

constexpr int L_ = 2048, D_ = 512, F_ = 1792, NS_ = 128;
constexpr int NCTA = 128;
constexpr int NTHREADS = 384;

constexpr int SM_X = 0;
constexpr int SM_RING = 131072;
constexpr int KC_STRIDE = 656;
constexpr int SM_KB = 212992;
constexpr int SM_PR = SM_KB + 4 * KC_STRIDE * 2;
constexpr int PR_WARP = 64 * 24;
constexpr int SM_BAR = SM_PR + 8 * PR_WARP;
constexpr int SM_TOTAL = SM_BAR + 512;
constexpr int CV_R = 0;
constexpr int R_HALF = 156 * 16;
constexpr int R_CH = 2 * R_HALF;
constexpr int CV_E = 4 * R_CH;
constexpr int E_COPY = 4160;
constexpr int E_CH = 2 * E_COPY;
constexpr int CV_S = CV_E + 4 * E_CH;
constexpr int S_PITCH = 136;
constexpr int S_WG = 4 * 16 * S_PITCH * 4;
constexpr int SM_AT = SM_X;
static_assert(CV_S + 2 * S_WG <= 131072, "conv region");

constexpr int B_FULL = 0, B_EMPTY = 5, B_XFULL = 10, B_XFREE = 18, B_ATILE = 26, B_RRDY = 27, B_ADONE = 28, B_SENT = 35, B_GOT = 43, B_STF = 51;

__device__ uint4 g_part[16 * 8 * 8 * 8 * 4 * 32];
__device__ uint32_t g_flag[16 * 8 * 8];
__device__ __align__(1024) __nv_bfloat16 g_aT[D_ * L_];
__device__ float g_gate[L_];
__device__ uint32_t g_done1;
__device__ uint32_t g_cnt[8 * 32];
__device__ uint32_t g_exit;
__device__ uint32_t g_zero;
__device__ uint32_t g_epoch;

#define TM_IF(cond, idx) do {} while (0)
#define FAIL(a, ph) break
#define SPIN_LIMIT (1 << 22)
#define MBAR_LIMIT (1 << 20)
__device__ __forceinline__ uint32_t smem_u32(const void* p) { return (uint32_t)__cvta_generic_to_shared(p); }
__device__ __forceinline__ void mbar_init(uint32_t a, uint32_t c) { asm volatile("mbarrier.init.shared::cta.b64 [%0], %1;" ::"r"(a), "r"(c) : "memory"); }
__device__ __forceinline__ void mbar_expect(uint32_t a, uint32_t bytes) { asm volatile("mbarrier.arrive.expect_tx.shared::cta.b64 _, [%0], %1;" ::"r"(a), "r"(bytes) : "memory"); }
__device__ __forceinline__ void mbar_arrive(uint32_t a) { asm volatile("mbarrier.arrive.shared::cta.b64 _, [%0];" ::"r"(a) : "memory"); }
__device__ __forceinline__ void mbar_wait(uint32_t a, uint32_t ph) {
  asm volatile("{\n.reg .pred p;\n.reg .u32 c;\nmov.u32 c, 0;\nLW:\nmbarrier.try_wait.parity.shared::cta.b64 p, [%0], %1, %2;\n@p bra LD;\n"
               "add.u32 c, c, 1;\nsetp.lt.u32 p, c, 1048576;\n@p bra LW;\nLD:\n}" ::"r"(a), "r"(ph), "r"(20000u) : "memory");
}
__device__ __forceinline__ void tma2d(uint32_t dst, const CUtensorMap* m, int c0, int c1, uint32_t bar) {
  asm volatile("cp.async.bulk.tensor.2d.shared::cluster.global.mbarrier::complete_tx::bytes [%0], [%1, {%3,%4}], [%2];" ::"r"(dst), "l"(m), "r"(bar), "r"(c0), "r"(c1) : "memory");
}
__device__ __forceinline__ void tma3d(uint32_t dst, const CUtensorMap* m, int c0, int c1, int c2, uint32_t bar) {
  asm volatile("cp.async.bulk.tensor.3d.shared::cluster.global.mbarrier::complete_tx::bytes [%0], [%1, {%3,%4,%5}], [%2];" ::"r"(dst), "l"(m), "r"(bar), "r"(c0), "r"(c1), "r"(c2) : "memory");
}
__device__ __forceinline__ uint64_t mkdesc(uint32_t addr, uint32_t lbo, uint32_t sbo, uint32_t sw) {
  return (uint64_t)((addr & 0x3FFFF) >> 4) | ((uint64_t)(lbo >> 4) << 16) | ((uint64_t)(sbo >> 4) << 32) | ((uint64_t)sw << 62);
}
__device__ __forceinline__ void wg_fence() { asm volatile("wgmma.fence.sync.aligned;" ::: "memory"); }
__device__ __forceinline__ void wg_commit() { asm volatile("wgmma.commit_group.sync.aligned;" ::: "memory"); }
template <int N> __device__ __forceinline__ void wg_wait() { asm volatile("wgmma.wait_group.sync.aligned %0;" ::"n"(N) : "memory"); }
__device__ __forceinline__ void zero_reg(float& x) { asm volatile("mov.f32 %0, 0f00000000;" : "=f"(x)); }
__device__ __forceinline__ void bar_sync(int id, int n) { asm volatile("bar.sync %0, %1;" ::"r"(id), "r"(n) : "memory"); }
__device__ __forceinline__ void fence_async() { asm volatile("fence.proxy.async.shared::cta;" ::: "memory"); }
__device__ __forceinline__ uint32_t pack_bf16(float lo, float hi) {
  uint32_t r;
  asm("cvt.rn.bf16x2.f32 %0, %1, %2;" : "=r"(r) : "f"(hi), "f"(lo));
  return r;
}
__device__ __forceinline__ uint32_t hmul2_bf16(uint32_t a, uint32_t b) {
  uint32_t r;
  asm("mul.rn.bf16x2 %0, %1, %2;" : "=r"(r) : "r"(a), "r"(b));
  return r;
}
__device__ __forceinline__ uint32_t hadd2_bf16(uint32_t a, uint32_t b) {
  uint32_t r;
  asm("add.rn.bf16x2 %0, %1, %2;" : "=r"(r) : "r"(a), "r"(b));
  return r;
}
__device__ __forceinline__ float bf_lo(uint32_t v) { return __uint_as_float(v << 16); }
__device__ __forceinline__ float bf_hi(uint32_t v) { return __uint_as_float(v & 0xFFFF0000u); }
__device__ __forceinline__ float bf16r(float x) { return __bfloat162float(__float2bfloat16_rn(x)); }
__device__ __forceinline__ float ldbf(const __nv_bfloat16* p) { return __bfloat162float(*p); }
__device__ __forceinline__ uint32_t ld_acquire(const uint32_t* p) {
  uint32_t v;
  asm volatile("ld.acquire.gpu.global.u32 %0, [%1];" : "=r"(v) : "l"(p) : "memory");
  return v;
}
__device__ __forceinline__ void st_release(uint32_t* p, uint32_t v) { asm volatile("st.release.gpu.global.u32 [%0], %1;" ::"l"(p), "r"(v) : "memory"); }
__device__ __forceinline__ uint4 ld_cg4(const uint4* p) {
  uint4 v;
  asm volatile("ld.global.cg.v4.u32 {%0,%1,%2,%3}, [%4];" : "=r"(v.x), "=r"(v.y), "=r"(v.z), "=r"(v.w) : "l"(p) : "memory");
  return v;
}
__device__ __forceinline__ uint32_t ld_cg1(const void* p) {
  uint32_t v;
  asm volatile("ld.global.cg.u32 %0, [%1];" : "=r"(v) : "l"(p) : "memory");
  return v;
}
__device__ __forceinline__ uint32_t lds32(uint32_t a) {
  uint32_t v;
  asm volatile("ld.shared.u32 %0, [%1];" : "=r"(v) : "r"(a) : "memory");
  return v;
}
__device__ __forceinline__ void ldsm4(uint32_t (&r)[4], uint32_t a) {
  asm volatile("ldmatrix.sync.aligned.m8n8.x4.shared.b16 {%0,%1,%2,%3}, [%4];" : "=r"(r[0]), "=r"(r[1]), "=r"(r[2]), "=r"(r[3]) : "r"(a) : "memory");
}
__device__ __forceinline__ uint32_t pack_f16(float lo, float hi) {
  uint32_t r;
  asm("cvt.rn.f16x2.f32 %0, %1, %2;" : "=r"(r) : "f"(hi), "f"(lo));
  return r;
}

__device__ __forceinline__ void wgmma_ss_n256(float (&d)[128], uint64_t da, uint64_t db) {
  asm volatile("wgmma.mma_async.sync.aligned.m64n256k16.f32.bf16.bf16 {%0, %1, %2, %3, %4, %5, %6, %7, %8, %9, %10, %11, %12, %13, %14, %15, %16, %17, %18, %19, %20, %21, %22, %23, %24, %25, %26, %27, %28, %29, %30, %31, %32, %33, %34, %35, %36, %37, %38, %39, %40, %41, %42, %43, %44, %45, %46, %47, %48, %49, %50, %51, %52, %53, %54, %55, %56, %57, %58, %59, %60, %61, %62, %63, %64, %65, %66, %67, %68, %69, %70, %71, %72, %73, %74, %75, %76, %77, %78, %79, %80, %81, %82, %83, %84, %85, %86, %87, %88, %89, %90, %91, %92, %93, %94, %95, %96, %97, %98, %99, %100, %101, %102, %103, %104, %105, %106, %107, %108, %109, %110, %111, %112, %113, %114, %115, %116, %117, %118, %119, %120, %121, %122, %123, %124, %125, %126, %127}, %128, %129, 1, 1, 1, 0, 1;"
    : "+f"(d[0]), "+f"(d[1]), "+f"(d[2]), "+f"(d[3]), "+f"(d[4]), "+f"(d[5]), "+f"(d[6]), "+f"(d[7]), "+f"(d[8]), "+f"(d[9]), "+f"(d[10]), "+f"(d[11]), "+f"(d[12]), "+f"(d[13]), "+f"(d[14]), "+f"(d[15]), "+f"(d[16]), "+f"(d[17]), "+f"(d[18]), "+f"(d[19]), "+f"(d[20]), "+f"(d[21]), "+f"(d[22]), "+f"(d[23]), "+f"(d[24]), "+f"(d[25]), "+f"(d[26]), "+f"(d[27]), "+f"(d[28]), "+f"(d[29]), "+f"(d[30]), "+f"(d[31]), "+f"(d[32]), "+f"(d[33]), "+f"(d[34]), "+f"(d[35]), "+f"(d[36]), "+f"(d[37]), "+f"(d[38]), "+f"(d[39]), "+f"(d[40]), "+f"(d[41]), "+f"(d[42]), "+f"(d[43]), "+f"(d[44]), "+f"(d[45]), "+f"(d[46]), "+f"(d[47]), "+f"(d[48]), "+f"(d[49]), "+f"(d[50]), "+f"(d[51]), "+f"(d[52]), "+f"(d[53]), "+f"(d[54]), "+f"(d[55]), "+f"(d[56]), "+f"(d[57]), "+f"(d[58]), "+f"(d[59]), "+f"(d[60]), "+f"(d[61]), "+f"(d[62]), "+f"(d[63]), "+f"(d[64]), "+f"(d[65]), "+f"(d[66]), "+f"(d[67]), "+f"(d[68]), "+f"(d[69]), "+f"(d[70]), "+f"(d[71]), "+f"(d[72]), "+f"(d[73]), "+f"(d[74]), "+f"(d[75]), "+f"(d[76]), "+f"(d[77]), "+f"(d[78]), "+f"(d[79]), "+f"(d[80]), "+f"(d[81]), "+f"(d[82]), "+f"(d[83]), "+f"(d[84]), "+f"(d[85]), "+f"(d[86]), "+f"(d[87]), "+f"(d[88]), "+f"(d[89]), "+f"(d[90]), "+f"(d[91]), "+f"(d[92]), "+f"(d[93]), "+f"(d[94]), "+f"(d[95]), "+f"(d[96]), "+f"(d[97]), "+f"(d[98]), "+f"(d[99]), "+f"(d[100]), "+f"(d[101]), "+f"(d[102]), "+f"(d[103]), "+f"(d[104]), "+f"(d[105]), "+f"(d[106]), "+f"(d[107]), "+f"(d[108]), "+f"(d[109]), "+f"(d[110]), "+f"(d[111]), "+f"(d[112]), "+f"(d[113]), "+f"(d[114]), "+f"(d[115]), "+f"(d[116]), "+f"(d[117]), "+f"(d[118]), "+f"(d[119]), "+f"(d[120]), "+f"(d[121]), "+f"(d[122]), "+f"(d[123]), "+f"(d[124]), "+f"(d[125]), "+f"(d[126]), "+f"(d[127]) : "l"(da), "l"(db));
}
__device__ __forceinline__ void wgmma_ss_n96(float (&d)[48], uint64_t da, uint64_t db) {
  asm volatile("wgmma.mma_async.sync.aligned.m64n96k16.f32.bf16.bf16 {%0, %1, %2, %3, %4, %5, %6, %7, %8, %9, %10, %11, %12, %13, %14, %15, %16, %17, %18, %19, %20, %21, %22, %23, %24, %25, %26, %27, %28, %29, %30, %31, %32, %33, %34, %35, %36, %37, %38, %39, %40, %41, %42, %43, %44, %45, %46, %47}, %48, %49, 1, 1, 1, 0, 1;"
    : "+f"(d[0]), "+f"(d[1]), "+f"(d[2]), "+f"(d[3]), "+f"(d[4]), "+f"(d[5]), "+f"(d[6]), "+f"(d[7]), "+f"(d[8]), "+f"(d[9]), "+f"(d[10]), "+f"(d[11]), "+f"(d[12]), "+f"(d[13]), "+f"(d[14]), "+f"(d[15]), "+f"(d[16]), "+f"(d[17]), "+f"(d[18]), "+f"(d[19]), "+f"(d[20]), "+f"(d[21]), "+f"(d[22]), "+f"(d[23]), "+f"(d[24]), "+f"(d[25]), "+f"(d[26]), "+f"(d[27]), "+f"(d[28]), "+f"(d[29]), "+f"(d[30]), "+f"(d[31]), "+f"(d[32]), "+f"(d[33]), "+f"(d[34]), "+f"(d[35]), "+f"(d[36]), "+f"(d[37]), "+f"(d[38]), "+f"(d[39]), "+f"(d[40]), "+f"(d[41]), "+f"(d[42]), "+f"(d[43]), "+f"(d[44]), "+f"(d[45]), "+f"(d[46]), "+f"(d[47]) : "l"(da), "l"(db));
}
__device__ __forceinline__ void wgmma_rs_n64t(float (&d)[32], uint32_t a0, uint32_t a1, uint32_t a2, uint32_t a3, uint64_t db) {
  asm volatile("wgmma.mma_async.sync.aligned.m64n64k16.f32.bf16.bf16 {%0, %1, %2, %3, %4, %5, %6, %7, %8, %9, %10, %11, %12, %13, %14, %15, %16, %17, %18, %19, %20, %21, %22, %23, %24, %25, %26, %27, %28, %29, %30, %31}, {%32,%33,%34,%35}, %36, 1, 1, 1, 1;"
    : "+f"(d[0]), "+f"(d[1]), "+f"(d[2]), "+f"(d[3]), "+f"(d[4]), "+f"(d[5]), "+f"(d[6]), "+f"(d[7]), "+f"(d[8]), "+f"(d[9]), "+f"(d[10]), "+f"(d[11]), "+f"(d[12]), "+f"(d[13]), "+f"(d[14]), "+f"(d[15]), "+f"(d[16]), "+f"(d[17]), "+f"(d[18]), "+f"(d[19]), "+f"(d[20]), "+f"(d[21]), "+f"(d[22]), "+f"(d[23]), "+f"(d[24]), "+f"(d[25]), "+f"(d[26]), "+f"(d[27]), "+f"(d[28]), "+f"(d[29]), "+f"(d[30]), "+f"(d[31]) : "r"(a0), "r"(a1), "r"(a2), "r"(a3), "l"(db));
}
__device__ __forceinline__ void wgmma_conv32(float (&d)[16], uint32_t a0, uint32_t a1, uint32_t a2, uint32_t a3, uint64_t db) {
  asm volatile("wgmma.mma_async.sync.aligned.m64n32k16.f32.bf16.bf16 {%0, %1, %2, %3, %4, %5, %6, %7, %8, %9, %10, %11, %12, %13, %14, %15}, {%16,%17,%18,%19}, %20, 1, 1, 1, 0;"
    : "+f"(d[0]), "+f"(d[1]), "+f"(d[2]), "+f"(d[3]), "+f"(d[4]), "+f"(d[5]), "+f"(d[6]), "+f"(d[7]), "+f"(d[8]), "+f"(d[9]), "+f"(d[10]), "+f"(d[11]), "+f"(d[12]), "+f"(d[13]), "+f"(d[14]), "+f"(d[15]) : "r"(a0), "r"(a1), "r"(a2), "r"(a3), "l"(db));
}
__device__ __forceinline__ void wgmma_conv32z(float (&d)[16], uint32_t a0, uint32_t a1, uint32_t a2, uint32_t a3, uint64_t db) {
  asm volatile("{.reg .pred p; setp.ne.b32 p, 0, 0; wgmma.mma_async.sync.aligned.m64n32k16.f32.bf16.bf16 {%0, %1, %2, %3, %4, %5, %6, %7, %8, %9, %10, %11, %12, %13, %14, %15}, {%16,%17,%18,%19}, %20, p, 1, 1, 0;}"
    : "=f"(d[0]), "=f"(d[1]), "=f"(d[2]), "=f"(d[3]), "=f"(d[4]), "=f"(d[5]), "=f"(d[6]), "=f"(d[7]), "=f"(d[8]), "=f"(d[9]), "=f"(d[10]), "=f"(d[11]), "=f"(d[12]), "=f"(d[13]), "=f"(d[14]), "=f"(d[15]) : "r"(a0), "r"(a1), "r"(a2), "r"(a3), "l"(db));
}
__device__ __forceinline__ void wgmma_rs_n64tz(float (&d)[32], uint32_t a0, uint32_t a1, uint32_t a2, uint32_t a3, uint64_t db) {
  asm volatile("{.reg .pred p; setp.ne.b32 p, 0, 0; wgmma.mma_async.sync.aligned.m64n64k16.f32.bf16.bf16 {%0, %1, %2, %3, %4, %5, %6, %7, %8, %9, %10, %11, %12, %13, %14, %15, %16, %17, %18, %19, %20, %21, %22, %23, %24, %25, %26, %27, %28, %29, %30, %31}, {%32,%33,%34,%35}, %36, p, 1, 1, 1;}"
    : "=f"(d[0]), "=f"(d[1]), "=f"(d[2]), "=f"(d[3]), "=f"(d[4]), "=f"(d[5]), "=f"(d[6]), "=f"(d[7]), "=f"(d[8]), "=f"(d[9]), "=f"(d[10]), "=f"(d[11]), "=f"(d[12]), "=f"(d[13]), "=f"(d[14]), "=f"(d[15]), "=f"(d[16]), "=f"(d[17]), "=f"(d[18]), "=f"(d[19]), "=f"(d[20]), "=f"(d[21]), "=f"(d[22]), "=f"(d[23]), "=f"(d[24]), "=f"(d[25]), "=f"(d[26]), "=f"(d[27]), "=f"(d[28]), "=f"(d[29]), "=f"(d[30]), "=f"(d[31]) : "r"(a0), "r"(a1), "r"(a2), "r"(a3), "l"(db));
}

struct cpx { float r, i; };
__device__ __forceinline__ cpx cmul(cpx a, cpx b) { return {fmaf(a.r, b.r, -a.i * b.i), fmaf(a.r, b.i, a.i * b.r)}; }
__device__ __forceinline__ cpx csqr(cpx a) { return {fmaf(a.r, a.r, -a.i * a.i), 2.f * a.r * a.i}; }
__device__ __forceinline__ cpx cexp_fast(float re, float im) {
  float e;
  asm("ex2.approx.ftz.f32 %0, %1;" : "=f"(e) : "f"(re * 1.4426950408889634f));
  float k = rintf(im * 0.15915494309189535f);
  float r = fmaf(k, -6.2831854820251465f, im);
  r = fmaf(k, 1.7484555314695172e-07f, r);
  float s, c;
  asm("sin.approx.f32 %0, %1;" : "=f"(s) : "f"(r));
  asm("cos.approx.f32 %0, %1;" : "=f"(c) : "f"(r));
  return {e * c, e * s};
}

struct KOps { uint32_t xa[5], xb[5], y[4]; };
__device__ __forceinline__ void kgen_ops(KOps& o, const float4 pr, const float2 qq, const float gf) {
  const cpx C = {pr.z, pr.w};
  const cpx Q = {qq.x, qq.y};
  const cpx V0 = cexp_fast(pr.x * gf, pr.y * gf);
  const cpx V1 = csqr(V0), V2 = csqr(V1), V3 = csqr(V2);
  const cpx Y0 = cmul(C, V0), Y1 = cmul(C, V1), Y2 = cmul(C, V2), Y3 = cmul(C, V3);
  o.y[0] = pack_f16(Y0.r, -Y0.i); o.y[1] = pack_f16(Y1.r, -Y1.i); o.y[2] = pack_f16(Y2.r, -Y2.i); o.y[3] = pack_f16(Y3.r, -Y3.i);
  const cpx Xb = cmul(V3, Q);
  cpx Xc = cmul(Xb, Q), Xd = cmul(Xc, Q);
  o.xa[0] = pack_f16(V3.r, V3.i); o.xb[0] = pack_f16(Xb.r, Xb.i);
  o.xa[1] = pack_f16(Xc.r, Xc.i); o.xb[1] = pack_f16(Xd.r, Xd.i);
#pragma unroll
  for (int k = 2; k < 5; k++) {
    Xc = csqr(Xc); Xd = csqr(Xd);
    o.xa[k] = pack_f16(Xc.r, Xc.i); o.xb[k] = pack_f16(Xd.r, Xd.i);
  }
}
__device__ __forceinline__ void kgen_mma(float (&T)[5][4], const KOps& a, const KOps& b) {
  asm("mma.sync.aligned.m16n8k16.row.col.f32.f16.f16.f32 {%0,%1,%2,%3}, {%20,%21,%22,%23}, {%40,%41}, {%0,%1,%2,%3};\n"
      "mma.sync.aligned.m16n8k16.row.col.f32.f16.f16.f32 {%4,%5,%6,%7}, {%24,%25,%26,%27}, {%40,%41}, {%4,%5,%6,%7};\n"
      "mma.sync.aligned.m16n8k16.row.col.f32.f16.f16.f32 {%8,%9,%10,%11}, {%28,%29,%30,%31}, {%42,%43}, {%8,%9,%10,%11};\n"
      "mma.sync.aligned.m16n8k16.row.col.f32.f16.f16.f32 {%12,%13,%14,%15}, {%32,%33,%34,%35}, {%44,%45}, {%12,%13,%14,%15};\n"
      "mma.sync.aligned.m16n8k16.row.col.f32.f16.f16.f32 {%16,%17,%18,%19}, {%36,%37,%38,%39}, {%46,%47}, {%16,%17,%18,%19};\n"
      : "+f"(T[0][0]), "+f"(T[0][1]), "+f"(T[0][2]), "+f"(T[0][3]), "+f"(T[1][0]), "+f"(T[1][1]), "+f"(T[1][2]), "+f"(T[1][3]),
        "+f"(T[2][0]), "+f"(T[2][1]), "+f"(T[2][2]), "+f"(T[2][3]), "+f"(T[3][0]), "+f"(T[3][1]), "+f"(T[3][2]), "+f"(T[3][3]),
        "+f"(T[4][0]), "+f"(T[4][1]), "+f"(T[4][2]), "+f"(T[4][3])
      : "r"(a.xa[0]), "r"(a.xb[0]), "r"(b.xa[0]), "r"(b.xb[0]), "r"(a.xa[1]), "r"(a.xb[1]), "r"(b.xa[1]), "r"(b.xb[1]),
        "r"(a.xa[2]), "r"(a.xb[2]), "r"(b.xa[2]), "r"(b.xb[2]), "r"(a.xa[3]), "r"(a.xb[3]), "r"(b.xa[3]), "r"(b.xb[3]),
        "r"(a.xa[4]), "r"(a.xb[4]), "r"(b.xa[4]), "r"(b.xb[4]),
        "r"(a.y[0]), "r"(b.y[0]), "r"(a.y[1]), "r"(b.y[1]), "r"(a.y[2]), "r"(b.y[2]), "r"(a.y[3]), "r"(b.y[3]));
}

template <int J> __device__ __forceinline__ void conv_issue(float (&acc)[4][16], const uint32_t (&f)[4], uint64_t db) {
  constexpr int NT = 4 - (J >> 3);
#pragma unroll
  for (int t = 0; t < NT; t++) {
    if (J == 0) wgmma_conv32z(acc[t], f[0], f[1], f[2], f[3], db + 4 * J + 32 * t);
    else wgmma_conv32(acc[t], f[0], f[1], f[2], f[3], db + 4 * J + 32 * t);
  }
}
template <int J0> __device__ __forceinline__ void conv_load4(uint32_t (&f)[4][4], uint32_t ebase, uint32_t zero) {
#pragma unroll
  for (int t = 0; t < 4; t++) {
    f[t][0] = lds32(ebase + (J0 + t) * 128);
    f[t][1] = lds32(ebase + (J0 + t) * 128 + 16);
    f[t][3] = lds32(ebase + (J0 + t) * 128 + 32);
  }
#pragma unroll
  for (int t = 0; t < 4; t++) f[t][2] = f[t][1] ^ zero;
}
template <int J0> __device__ __forceinline__ void conv_issue4(float (&acc)[4][16], const uint32_t (&f)[4][4], uint64_t db) {
  wg_fence();
  conv_issue<J0 + 0>(acc, f[0], db);
  conv_issue<J0 + 1>(acc, f[1], db);
  conv_issue<J0 + 2>(acc, f[2], db);
  conv_issue<J0 + 3>(acc, f[3], db);
  wg_commit();
}

template <int V> struct IC { static constexpr int value = V; };

struct Params {
  const __nv_bfloat16* x;
  const __nv_bfloat16* log_A_real;
  const __nv_bfloat16* A_imag;
  const __nv_bfloat16* C_real;
  const __nv_bfloat16* C_imag;
  const __nv_bfloat16* log_dt;
  const __nv_bfloat16* D_skip;
  const __nv_bfloat16* gate_w;
  const __nv_bfloat16* w_gate;
  const __nv_bfloat16* w_up;
  const __nv_bfloat16* w_down;
  __nv_bfloat16* out;
};

struct Maps {
  CUtensorMap X, Wg, Wu, Wg3[2], Wu3[2], Wd, AT;
};

__device__ __forceinline__ uint32_t ld_epoch() { return *(volatile uint32_t*)&g_epoch; }
__device__ __forceinline__ uint32_t dup_lo(uint32_t w) { return __byte_perm(w, w, 0x1010); }
__device__ __forceinline__ uint32_t dup_hi(uint32_t w) { return __byte_perm(w, w, 0x3232); }

__global__ void __cluster_dims__(2, 1, 1) __launch_bounds__(NTHREADS, 1)
fused_kernel(const __grid_constant__ Maps M, const Params P) {
  extern __shared__ __align__(1024) uint8_t smem[];
  const uint32_t sb = smem_u32(smem);
  const uint32_t bars = sb + SM_BAR;
  const int tid = threadIdx.x;
  const int warp = __shfl_sync(0xffffffffu, tid >> 5, 0), lane = tid & 31;
  const int b = blockIdx.x;
  const int cl = b >> 1;
  const int jf = cl & 7;
  const int it_ = ((cl >> 3) << 1) | (b & 1);
  const int d0 = b * 4;

  uint32_t pw0[2] = {0, 0}, pw1[2] = {0, 0}, pldt = 0;
  if (warp < 8) {
#pragma unroll
    for (int r = 0; r < 2; r++) {
      const int n = (d0 + (warp >> 1)) * NS_ + 64 * (warp & 1) + lane + 32 * r;
      pw0[r] = (uint32_t)*(const unsigned short*)(P.log_A_real + n) | ((uint32_t)*(const unsigned short*)(P.A_imag + n) << 16);
      pw1[r] = (uint32_t)*(const unsigned short*)(P.C_real + n) | ((uint32_t)*(const unsigned short*)(P.C_imag + n) << 16);
    }
    pldt = *(const unsigned short*)(P.log_dt + d0 + (warp >> 1));
  }
  if (tid == 256) {
    asm volatile("prefetch.tensormap [%0];" ::"l"(&M.X) : "memory");
    asm volatile("prefetch.tensormap [%0];" ::"l"(&M.Wg3[jf & 1]) : "memory");
    asm volatile("prefetch.tensormap [%0];" ::"l"(&M.Wu3[jf & 1]) : "memory");
    for (int i = 0; i < 5; i++) { mbar_init(bars + 8 * (B_FULL + i), 1); mbar_init(bars + 8 * (B_EMPTY + i), 8); }
    for (int i = 0; i < 8; i++) { mbar_init(bars + 8 * (B_XFULL + i), 1); mbar_init(bars + 8 * (B_XFREE + i), 8); mbar_init(bars + 8 * (B_SENT + i), 8); }
    mbar_init(bars + 8 * B_RRDY, 3);
    mbar_init(bars + 8 * B_ADONE, 8);
    for (int i = 1; i < 8; i++) mbar_init(bars + 8 * (B_GOT + i), 1);
    for (int i = 0; i < 7; i++) mbar_init(bars + 8 * (B_STF + i), 1);
    mbar_init(bars + 8 * B_ATILE, 1);
    asm volatile("fence.mbarrier_init.release.cluster;" ::: "memory");
    fence_async();
  }
  __syncthreads();

  if (warp >= 8) {
    asm volatile("setmaxnreg.dec.sync.aligned.u32 104;");
    if (warp == 8) {
      if (lane == 0) {
#pragma unroll 1
        for (int s = 0; s < 48; s++) {
          const int slot = s % 5;
          if (s < 16 && (s & 1) == 0) {
            const int kb = s >> 1;
            mbar_expect(bars + 8 * (B_XFULL + kb), 16384);
            tma2d(sb + SM_X + kb * 16384, &M.X, kb * 64, it_ * 128, bars + 8 * (B_XFULL + kb));
          }
          if (s >= 5) mbar_wait(bars + 8 * (B_EMPTY + slot), ((s / 5) - 1) & 1);
          const uint32_t dst = sb + SM_RING + slot * 16384;
          const uint32_t fb = bars + 8 * (B_FULL + slot);
          if (s < 32) {
            const int f0 = jf * 224 + ((s >> 4) << 7);
            const int k0 = (s & 15) * 32;
            mbar_expect(fb, 16384);
            if (jf == 7 && s >= 16) {
              tma2d(dst, &M.Wg, f0, k0, fb);
              tma2d(dst + 4096, &M.Wg, f0 + 64, k0, fb);
              tma2d(dst + 8192, &M.Wu, f0, k0, fb);
              tma2d(dst + 12288, &M.Wu, f0 + 64, k0, fb);
            } else {
              tma3d(dst, &M.Wg3[jf & 1], 0, k0, f0 >> 6, fb);
              tma3d(dst + 8192, &M.Wu3[jf & 1], 0, k0, f0 >> 6, fb);
            }
          } else {
            const int s2 = s - 32;
            const int p = (jf + 1 + (s2 >> 1)) & 7;
            mbar_expect(fb, 14336);
            tma2d(dst, &M.Wd, p * 64, jf * 224 + (s2 & 1) * 112, fb);
          }
        }
      }
      __syncwarp();
      if (lane >= 1 && lane < 8) {
        const uint32_t tag = ld_epoch() + 1;
        const uint32_t* fp = g_flag + ((it_ * 8 + jf) * 8 + ((jf - lane) & 7));
        int itc = 0;
        while (ld_acquire(fp) != tag) { __nanosleep(40); if (++itc > SPIN_LIMIT) FAIL(-2, lane); }
        mbar_arrive(bars + 8 * (B_GOT + lane));
        TM_IF(lane == 7, 25);
      }
      __syncwarp();
    } else {
      const int w = warp - 9;
      const int wt = tid - 288;
      {
        const uint4 gw0 = *(const uint4*)(P.gate_w + lane * 16);
        const uint4 gw1 = *(const uint4*)(P.gate_w + lane * 16 + 8);
        uint4 xa[6], xb[6];
#pragma unroll
        for (int i = 0; i < 6; i++) {
          int rr = w + 3 * i; rr = rr < 16 ? rr : 15;
          xa[i] = *(const uint4*)(P.x + (b * 16 + rr) * D_ + lane * 16);
          xb[i] = *(const uint4*)(P.x + (b * 16 + rr) * D_ + lane * 16 + 8);
        }
        float sg[6];
#pragma unroll
        for (int i = 0; i < 6; i++) {
          const uint32_t pr[8] = {hmul2_bf16(xa[i].x, gw0.x), hmul2_bf16(xa[i].y, gw0.y), hmul2_bf16(xa[i].z, gw0.z), hmul2_bf16(xa[i].w, gw0.w),
                                  hmul2_bf16(xb[i].x, gw1.x), hmul2_bf16(xb[i].y, gw1.y), hmul2_bf16(xb[i].z, gw1.z), hmul2_bf16(xb[i].w, gw1.w)};
          float s = 0.f;
#pragma unroll
          for (int k = 0; k < 8; k++) s += bf_lo(pr[k]) + bf_hi(pr[k]);
          sg[i] = s;
        }
#pragma unroll
        for (int o = 16; o > 0; o >>= 1) {
#pragma unroll
          for (int i = 0; i < 6; i++) sg[i] += __shfl_xor_sync(0xffffffffu, sg[i], o);
        }
        float z = sg[0];
#pragma unroll
        for (int i = 1; i < 6; i++) z = (lane == i) ? sg[i] : z;
        const int rr = w + 3 * lane;
        if (lane < 6 && rr < 16) g_gate[b * 16 + rr] = bf16r(1.f / (1.f + expf(-bf16r(z))));
      }
      bar_sync(1, 96);
      if (wt == 64) asm volatile("red.release.gpu.global.add.u32 [%0], 1;" ::"l"(&g_done1) : "memory");
      TM_IF(wt == 0, 16);
      {
        mbar_wait(bars + 8 * (B_XFULL + 3), 0);
        const uint32_t zz = *(volatile uint32_t*)&g_zero;
        uint2 ur[3][8];
#pragma unroll
        for (int i = 0; i < 3; i++) {
          int item = wt + 96 * i; item = item < 256 ? item : 255;
#pragma unroll
          for (int r = 0; r < 8; r++) {
            uint32_t ck;
            asm volatile("nanosleep.u32 200;\n\tmov.u32 %0, %%clock;" : "=r"(ck) :: "memory");
            asm volatile("ld.global.nc.v2.u32 {%0,%1}, [%2];" : "=r"(ur[i][r].x), "=r"(ur[i][r].y)
                         : "l"(P.x + (item * 8 + r) * D_ + d0 + (ck & zz)));
          }
        }
        mbar_wait(bars + 8 * (B_XFREE + 7), 0);
        TM_IF(wt == 0, 18);
#pragma unroll
        for (int i = 0; i < 3; i++) {
          const int item = wt + 96 * i;
          if (item < 256) {
            const int c = item >> 1, hh = item & 1;
#pragma unroll
            for (int ch = 0; ch < 4; ch++) {
              uint32_t v[4];
#pragma unroll
              for (int k = 0; k < 4; k++) {
                const uint32_t lo = (ch < 2) ? ur[i][7 - 2 * k].x : ur[i][7 - 2 * k].y;
                const uint32_t hi = (ch < 2) ? ur[i][6 - 2 * k].x : ur[i][6 - 2 * k].y;
                v[k] = (ch & 1) ? __byte_perm(lo, hi, 0x7632) : __byte_perm(lo, hi, 0x5410);
              }
              *(uint4*)(smem + SM_X + CV_R + ch * R_CH + (1 - hh) * R_HALF + (127 - c) * 16) = make_uint4(v[0], v[1], v[2], v[3]);
            }
          }
        }
        for (int z = wt; z < 8 * 28; z += 96)
          *(uint4*)(smem + SM_X + CV_R + (z / 28) * R_HALF + (128 + (z % 28)) * 16) = make_uint4(0, 0, 0, 0);
      }
      {
#pragma unroll 1
      for (int G = (w == 0 ? 0 : 8); G < 8; G++) {
        const int n = 32 * G + lane;
        uint4 c0[4], c1[4];
        if (G >= 4) {
#pragma unroll
          for (int ch = 0; ch < 4; ch++) {
            const uint8_t* kc = smem + SM_KB + ch * KC_STRIDE * 2;
            const uint32_t a = *(const unsigned short*)(kc + (384 + n) * 2), bb = *(const unsigned short*)(kc + (385 + n) * 2);
            const uint32_t aa = a | (a << 16), b2 = bb | (bb << 16);
            const uint32_t tie = (n & 1) ? bb : a;
            c0[ch] = make_uint4(aa, a | (tie << 16), b2, b2);
            c1[ch] = make_uint4(aa, tie | (bb << 16), b2, b2);
          }
        } else if (G >= 2) {
#pragma unroll
          for (int ch = 0; ch < 4; ch++) {
            const uint8_t* kc = smem + SM_KB + ch * KC_STRIDE * 2;
            const uint32_t w0 = *(const uint32_t*)(kc + (256 + 2 * n) * 2), w1 = *(const uint32_t*)(kc + (258 + 2 * n) * 2);
            c0[ch] = make_uint4(dup_lo(w0), dup_hi(w0), __byte_perm(w0, w1, 0x5432), dup_lo(w1));
            c1[ch] = make_uint4(w0, dup_hi(w0), dup_lo(w1), dup_lo(w1));
          }
        } else if (G == 1) {
#pragma unroll
          for (int ch = 0; ch < 4; ch++) {
            const uint8_t* kc = smem + SM_KB + ch * KC_STRIDE * 2;
            const uint2 w01 = *(const uint2*)(kc + (128 + 4 * n) * 2);
            const uint32_t w2 = *(const uint32_t*)(kc + (132 + 4 * n) * 2);
            c0[ch] = make_uint4(w01.x, dup_lo(w01.y), w01.y, dup_lo(w2));
            c1[ch] = make_uint4(__byte_perm(w01.x, w01.y, 0x5432), dup_lo(w01.y), __byte_perm(w01.y, w2, 0x5432), dup_lo(w2));
          }
        } else {
#pragma unroll
          for (int ch = 0; ch < 4; ch++) {
            const uint8_t* kc = smem + SM_KB + ch * KC_STRIDE * 2;
            const uint4 wv = *(const uint4*)(kc + (8 * n) * 2);
            const uint32_t w4 = *(const uint32_t*)(kc + (8 * n + 8) * 2);
            c0[ch] = make_uint4(__byte_perm(wv.x, wv.y, 0x5432), __byte_perm(wv.y, wv.z, 0x5432), __byte_perm(wv.z, wv.w, 0x5432), __byte_perm(wv.w, w4, 0x5432));
            c1[ch] = make_uint4(wv.y, wv.z, wv.w, (n == 31) ? dup_lo(w4) : w4);
          }
          if (lane < 8) {
            const int ch = lane >> 1, hi = lane & 1;
            const uint32_t k01 = *(const uint32_t*)(smem + SM_KB + ch * KC_STRIDE * 2);
            uint8_t* e = smem + SM_X + CV_E + ch * E_CH + hi * 16;
            *(uint4*)e = make_uint4(0, 0, 0, hi ? (k01 << 16) : 0u);
            *(uint4*)(e + E_COPY) = make_uint4(0, 0, 0, hi ? k01 : 0u);
          }
        }
#pragma unroll
        for (int ch = 0; ch < 4; ch++) {
          uint8_t* e = smem + SM_X + CV_E + ch * E_CH + (n + 2) * 16;
          *(uint4*)e = c0[ch];
          *(uint4*)(e + E_COPY) = c1[ch];
        }
      }
        fence_async();
        __syncwarp();
        if (lane == 0) mbar_arrive(bars + 8 * B_RRDY);
        TM_IF(wt == 0, 19);
      }
      if (wt == 0) {
        const uint32_t tag = ld_epoch() + 1;
#pragma unroll 1
        for (int rnd = 0; rnd < 2; rnd++) {
          mbar_wait(bars + 8 * B_ADONE, rnd);
          TM_IF(true, 24);
#pragma unroll
          for (int v = 0; v < 2; v++)
            asm volatile("cp.async.bulk.global.shared::cta.bulk_group [%0], [%1], %2;"
                         ::"l"(g_aT + (d0 + 2 * v + rnd) * L_), "r"(sb + SM_X + CV_E + (2 * v + rnd) * E_CH), "r"(4096) : "memory");
          asm volatile("cp.async.bulk.commit_group;" ::: "memory");
          asm volatile("cp.async.bulk.wait_group 0;" ::: "memory");
          asm volatile("fence.proxy.async.global;" ::: "memory");
          asm volatile("red.release.gpu.global.add.u32 [%0], 1;" ::"l"(g_cnt + 32 * (b >> 4)) : "memory");
        }
        TM_IF(true, 26);
        {
          int itc = 0;
          while ((int)(ld_acquire(&g_done1) - (uint32_t)NCTA * tag) < 0) { if (++itc > SPIN_LIMIT) FAIL(-1, 0); }
          while ((int)(ld_acquire(g_cnt + 32 * jf) - 32u * tag) < 0) { if (++itc > SPIN_LIMIT) FAIL(-3, 0); }
        }
        TM_IF(true, 23);
        asm volatile("fence.proxy.async.global;" ::: "memory");
        TM_IF(true, 27);
        mbar_expect(bars + 8 * B_ATILE, 16384);
        tma2d(sb + SM_AT, &M.AT, it_ * 128, jf * 64, bars + 8 * B_ATILE);
        tma2d(sb + SM_AT + 8192, &M.AT, it_ * 128 + 64, jf * 64, bars + 8 * B_ATILE);
      }
      if (w >= 1 && lane == 0) {
        const uint32_t tag = ld_epoch() + 1;
#pragma unroll 1
        for (int s = w - 1; s < 7; s += 2) {
          mbar_wait(bars + 8 * (B_SENT + s), 0);
          const int fi = (it_ * 8 + ((jf + 1 + s) & 7)) * 8 + jf;
#pragma unroll
          for (int v = 0; v < 2; v++)
            asm volatile("cp.async.bulk.global.shared::cta.bulk_group [%0], [%1], %2;"
                         ::"l"(g_part + (size_t)fi * 1024 + v * 512), "r"(sb + SM_X + CV_S + v * S_WG + (s & 3) * 8192), "r"(8192) : "memory");
          asm volatile("cp.async.bulk.commit_group;" ::: "memory");
          asm volatile("cp.async.bulk.wait_group 0;" ::: "memory");
          mbar_arrive(bars + 8 * (B_STF + s));
          asm volatile("fence.proxy.async.global;" ::: "memory");
          st_release(g_flag + fi, tag);
          TM_IF(true, 3 + s);
        }
      }
      __syncwarp();
    }
    bar_sync(0, NTHREADS);
    TM_IF(tid == 256, 13);
  } else {
    asm volatile("setmaxnreg.inc.sync.aligned.u32 200;");
    const int wg = warp >> 2;
    const int g = lane >> 2, q = lane & 3;
    {
      const int ch = warp >> 1, hs = warp & 1;
      const float dtf = bf16r(expf(bf_lo(pldt)));
      float4* prm = (float4*)(smem + SM_PR + warp * PR_WARP);
      float2* prq = (float2*)(smem + SM_PR + warp * PR_WARP + 64 * 16);
      float m0 = fmaxf(fmaxf(fabsf(bf_lo(pw1[0])), fabsf(bf_hi(pw1[0]))), fmaxf(fabsf(bf_lo(pw1[1])), fabsf(bf_hi(pw1[1])))) * dtf;
#pragma unroll
      for (int o = 16; o > 0; o >>= 1) m0 = fmaxf(m0, __shfl_xor_sync(0xffffffffu, m0, o));
      TM_IF(tid == 0 && m0 >= 0.f, 0);
      const uint32_t e0 = min(max(__float_as_uint(m0) >> 23, 1u), 253u);
      const float sc = __uint_as_float((254u - e0) << 23);
      const float us = 2.f * __uint_as_float(e0 << 23);
      float pe = 0.f;
#pragma unroll
      for (int r = 0; r < 2; r++) {
        float4 v;
        v.x = -bf16r(expf(bf_lo(pw0[r]))) * dtf;
        v.y = bf_hi(pw0[r]) * dtf;
        v.z = bf_lo(pw1[r]) * dtf * sc;
        v.w = bf_hi(pw1[r]) * dtf * sc;
        const cpx Q = cexp_fast(v.x * 64.f, v.y * 64.f);
        const cpx We = cexp_fast(v.x * 2048.f, v.y * 2048.f);
        pe += v.z * We.r - v.w * We.i;
        prm[lane + 32 * r] = v;
        prq[lane + 32 * r] = make_float2(Q.r, Q.i);
      }
#pragma unroll
      for (int o = 16; o > 0; o >>= 1) pe += __shfl_xor_sync(0xffffffffu, pe, o);
      __syncwarp();
      TM_IF(tid == 0, 1);
      float T[5][4];
#pragma unroll
      for (int i = 0; i < 20; i++) T[i >> 2][i & 3] = 0.f;
      const float gf = (float)g;
#pragma unroll 2
      for (int ks = 0; ks < 8; ks++) {
        KOps o1, o2;
        kgen_ops(o1, prm[8 * ks + q], prq[8 * ks + q], gf);
        kgen_ops(o2, prm[8 * ks + 4 + q], prq[8 * ks + 4 + q], gf);
        kgen_mma(T, o1, o2);
      }
#pragma unroll
      for (int i = 0; i < 20; i++) T[i >> 2][i & 3] *= us;
      pe *= us;
      TM_IF(tid == 0 && T[0][0] != 123.f, 2);
      const int o = 8 * g + 2 * q;
      float* kp = (float*)(smem + SM_PR + (warp & ~1) * PR_WARP);
      bar_sync(2 + ch, 64);
      if (hs) {
#pragma unroll
        for (int k = 0; k < 5; k++) {
          *(float2*)(kp + 128 * k + o) = make_float2(T[k][0], T[k][1]);
          *(float2*)(kp + 128 * k + 64 + o) = make_float2(T[k][2], T[k][3]);
        }
        if (lane == 0) kp[640] = pe;
      }
      bar_sync(2 + ch, 64);
      if (!hs) {
        uint32_t* kc = (uint32_t*)(smem + SM_KB + (ch * KC_STRIDE + o) * 2);
#pragma unroll
        for (int k = 0; k < 5; k++) {
          const float2 a0 = *(const float2*)(kp + 128 * k + o), b0 = *(const float2*)(kp + 128 * k + 64 + o);
          kc[64 * k] = pack_bf16(T[k][0] + a0.x, T[k][1] + a0.y);
          kc[64 * k + 32] = pack_bf16(T[k][2] + b0.x, T[k][3] + b0.y);
        }
        if (lane == 0) kc[320] = pack_bf16(pe + kp[640], 0.f);
      }
    }
    const uint32_t dsk = *(const uint32_t*)(P.D_skip + d0 + 2 * wg);
    uint32_t hf[56];
    {
      float acc[128];
#pragma unroll
      for (int i = 0; i < 128; i++) zero_reg(acc[i]);
#pragma unroll 1
      for (int st = 0; st < 16; st++) {
        const int slot = st % 5;
        if ((st & 1) == 0) mbar_wait(bars + 8 * (B_XFULL + (st >> 1)), 0);
        mbar_wait(bars + 8 * (B_FULL + slot), (st / 5) & 1);
        const uint64_t da = mkdesc(sb + SM_X + (st >> 1) * 16384 + wg * 8192 + (st & 1) * 64, 16, 1024, 1);
        const uint64_t db = mkdesc(sb + SM_RING + slot * 16384, 4096, 1024, 1);
        wg_fence();
        wgmma_ss_n256(acc, da, db);
        wgmma_ss_n256(acc, da + 2, db + 128);
        wg_commit();
        if (st > 0) {
          wg_wait<1>();
          if (lane == 0) mbar_arrive(bars + 8 * (B_EMPTY + (st - 1) % 5));
        }
      }
      wg_wait<0>();
      if (lane == 0) mbar_arrive(bars + 8 * (B_EMPTY + 15 % 5));
#pragma unroll
      for (int m = 0; m < 16; m++) {
        hf[2 * m] = hmul2_bf16(pack_bf16(acc[4 * m], acc[4 * m + 1]), pack_bf16(acc[64 + 4 * m], acc[64 + 4 * m + 1]));
        hf[2 * m + 1] = hmul2_bf16(pack_bf16(acc[4 * m + 2], acc[4 * m + 3]), pack_bf16(acc[64 + 4 * m + 2], acc[64 + 4 * m + 3]));
      }
    }
    {
      float accg[48], accu[48];
#pragma unroll
      for (int i = 0; i < 48; i++) { zero_reg(accg[i]); zero_reg(accu[i]); }
#pragma unroll 1
      for (int st = 16; st < 32; st++) {
        const int slot = st % 5;
        const int sl = st - 16;
        mbar_wait(bars + 8 * (B_FULL + slot), (st / 5) & 1);
        const uint64_t da = mkdesc(sb + SM_X + (sl >> 1) * 16384 + wg * 8192 + (sl & 1) * 64, 16, 1024, 1);
        const uint64_t db = mkdesc(sb + SM_RING + slot * 16384, 4096, 1024, 1);
        wg_fence();
        wgmma_ss_n96(accg, da, db);
        wgmma_ss_n96(accu, da, db + 512);
        wgmma_ss_n96(accg, da + 2, db + 128);
        wgmma_ss_n96(accu, da + 2, db + 128 + 512);
        wg_commit();
        if (st > 16) {
          wg_wait<1>();
          if (lane == 0) {
            mbar_arrive(bars + 8 * (B_EMPTY + (st - 1) % 5));
            if ((sl & 1) == 0) mbar_arrive(bars + 8 * (B_XFREE + ((sl - 1) >> 1)));
          }
        }
      }
      wg_wait<0>();
      if (lane == 0) { mbar_arrive(bars + 8 * (B_EMPTY + 31 % 5)); mbar_arrive(bars + 8 * (B_XFREE + 7)); }
#pragma unroll
      for (int m = 0; m < 12; m++) {
        hf[32 + 2 * m] = hmul2_bf16(pack_bf16(accg[4 * m], accg[4 * m + 1]), pack_bf16(accu[4 * m], accu[4 * m + 1]));
        hf[32 + 2 * m + 1] = hmul2_bf16(pack_bf16(accg[4 * m + 2], accg[4 * m + 3]), pack_bf16(accu[4 * m + 2], accu[4 * m + 3]));
      }
    }
    float accA[32], accB[32];
    auto issue_half = [&](float (&acc)[32], int s, auto half_tag) {
      constexpr int half = decltype(half_tag)::value;
      if (half == 0) {
#pragma unroll
        for (int i = 0; i < 32; i++) zero_reg(acc[i]);
      }
      const int st = 32 + 2 * s + half;
      const int slot = st % 5;
      mbar_wait(bars + 8 * (B_FULL + slot), (st / 5) & 1);
      uint32_t sbase;
      asm volatile("mov.b32 %0, %1;" : "=r"(sbase) : "r"(sb + SM_RING + slot * 16384));
      const uint64_t db = mkdesc(sbase, 1024, 1024, 1);
      wg_fence();
#pragma unroll
      for (int k = 0; k < 7; k++) {
        const int ks = 7 * half + k;
        wgmma_rs_n64t(acc, hf[4 * ks], hf[4 * ks + 1], hf[4 * ks + 2], hf[4 * ks + 3], db + k * 128);
      }
      wg_commit();
    };
    auto release = [&](int st) { if (lane == 0) mbar_arrive(bars + 8 * (B_EMPTY + st % 5)); };
    using H0 = IC<0>;
    using H1 = IC<1>;
    auto send_pass = [&](float (&acc)[32], int s) {
      uint4* dst = (uint4*)(smem + SM_X + CV_S + wg * S_WG + (s & 3) * 8192 + (warp & 3) * 2048) + lane;
#pragma unroll
      for (int c = 0; c < 4; c++) {
        uint4 v;
        v.x = pack_bf16(acc[8 * c], acc[8 * c + 1]); v.y = pack_bf16(acc[8 * c + 2], acc[8 * c + 3]);
        v.z = pack_bf16(acc[8 * c + 4], acc[8 * c + 5]); v.w = pack_bf16(acc[8 * c + 6], acc[8 * c + 7]);
        dst[c * 32] = v;
      }
      fence_async();
      __syncwarp();
      if (lane == 0) mbar_arrive(bars + 8 * (B_SENT + s));
    };
    auto part_load = [&](uint4 (&v)[4], int k) {
      mbar_wait(bars + 8 * (B_GOT + k), 0);
      const uint4* sp = g_part + (size_t)(((it_ * 8 + jf) * 8 + ((jf - k) & 7)) * 8 + warp) * 128 + lane;
#pragma unroll
      for (int c = 0; c < 4; c++) v[c] = ld_cg4(sp + c * 32);
    };
    auto part_add = [&](const uint4 (&v)[4]) {
#pragma unroll
      for (int c = 0; c < 4; c++) {
        accA[8 * c] += bf_lo(v[c].x); accA[8 * c + 1] += bf_hi(v[c].x); accA[8 * c + 2] += bf_lo(v[c].y); accA[8 * c + 3] += bf_hi(v[c].y);
        accA[8 * c + 4] += bf_lo(v[c].z); accA[8 * c + 5] += bf_hi(v[c].z); accA[8 * c + 6] += bf_lo(v[c].w); accA[8 * c + 7] += bf_hi(v[c].w);
      }
    };
    mbar_wait(bars + 8 * (B_XFREE + 7), 0);
    issue_half(accA, 0, H0{});
    issue_half(accA, 0, H1{}); wg_wait<1>(); release(32);
    issue_half(accB, 1, H0{}); wg_wait<1>(); release(33); send_pass(accA, 0);
    issue_half(accB, 1, H1{}); wg_wait<1>(); release(34);
    issue_half(accA, 2, H0{}); wg_wait<1>(); release(35); send_pass(accB, 1);
    issue_half(accA, 2, H1{}); wg_wait<1>(); release(36);
    issue_half(accB, 3, H0{}); wg_wait<1>(); release(37); send_pass(accA, 2);
    issue_half(accB, 3, H1{}); wg_wait<1>(); release(38);
    issue_half(accA, 4, H0{}); wg_wait<1>(); release(39); send_pass(accB, 3);
    issue_half(accA, 4, H1{}); wg_wait<1>(); release(40);
    issue_half(accB, 5, H0{}); wg_wait<1>(); release(41); mbar_wait(bars + 8 * (B_STF + 0), 0); send_pass(accA, 4);
    issue_half(accB, 5, H1{}); wg_wait<1>(); release(42);
    wg_wait<0>(); mbar_wait(bars + 8 * (B_STF + 1), 0); send_pass(accB, 5);
    {
      TM_IF(tid == 0, 10);
      const int w = warp & 3;
      mbar_wait(bars + 8 * B_RRDY, 0);
      TM_IF(tid == 0, 11);
      const uint32_t zero = lds32(sb + SM_X + CV_R + 128 * 16);
      const int c = tid & 127;
      const float* Sr = (const float*)(smem + SM_X + CV_S + wg * S_WG) + (127 - c);
      float* Sw = (float*)(smem + SM_X + CV_S + wg * S_WG) + w * 16 * S_PITCH + g * S_PITCH + 2 * q;
      float acc[4][16];
      uint32_t fa[4][4], fb[4][4];
      uint32_t ares[8], rv[8];
      auto stage_out = [&]() {
#pragma unroll
        for (int m = 0; m < 16; m++) {
          *(float2*)(Sw + 8 * m) = make_float2(acc[m >> 2][4 * (m & 3)], acc[m >> 2][4 * (m & 3) + 1]);
          *(float2*)(Sw + 8 * S_PITCH + 8 * m) = make_float2(acc[m >> 2][4 * (m & 3) + 2], acc[m >> 2][4 * (m & 3) + 3]);
        }
      };
      auto load_u = [&](int ch) {
        const uint4 r0v = *(const uint4*)(smem + SM_X + CV_R + ch * R_CH + (127 - c) * 16);
        const uint4 r1v = *(const uint4*)(smem + SM_X + CV_R + ch * R_CH + R_HALF + (127 - c) * 16);
        rv[0] = r0v.x; rv[1] = r0v.y; rv[2] = r0v.z; rv[3] = r0v.w; rv[4] = r1v.x; rv[5] = r1v.y; rv[6] = r1v.z; rv[7] = r1v.w;
      };
#define POST(r2, dk2)                                                                              \
      {                                                                                            \
        float y_[2];                                                                               \
        _Pragma("unroll") for (int t2 = 0; t2 < 2; t2++) {                                         \
          const int r0 = 2 * (r2) + t2;                                                            \
          const float s1 = c >= 1 ? Sr[(16 + r0) * S_PITCH + 1] : 0.f;                             \
          const float s2 = c >= 2 ? Sr[(32 + r0) * S_PITCH + 2] : 0.f;                             \
          const float s3 = c >= 3 ? Sr[(48 + r0) * S_PITCH + 3] : 0.f;                             \
          y_[t2] = (Sr[r0 * S_PITCH] + s1) + (s2 + s3);                                            \
        }                                                                                          \
        ares[r2] = hadd2_bf16(pack_bf16(y_[0], y_[1]), hmul2_bf16(__byte_perm(rv[7 - (r2)], rv[7 - (r2)], 0x1032), dk2)); \
      }
      auto store_a = [&](int ch) {
        uint4* ap = (uint4*)(smem + SM_X + CV_E + ch * E_CH + c * 32);
        ap[0] = make_uint4(ares[0], ares[1], ares[2], ares[3]);
        ap[1] = make_uint4(ares[4], ares[5], ares[6], ares[7]);
        fence_async();
      };
      const uint32_t eoff = ((g & 1) ? E_COPY : 0) + (16 * w + (g & ~1) + 2 * q) * 2;
      const uint32_t dkA = dup_lo(dsk), dkB = dup_hi(dsk);
      {
        const int ch = 2 * wg;
        const uint32_t ebase = sb + SM_X + CV_E + ch * E_CH + eoff;
        const uint64_t de = mkdesc(sb + SM_X + CV_R + ch * R_CH, R_HALF, 128, 0);
        conv_load4<0>(fa, ebase, zero);
        conv_load4<4>(fb, ebase, zero);
        conv_issue4<0>(acc, fa, de);
        conv_issue4<4>(acc, fb, de);
        wg_wait<1>(); conv_load4<8>(fa, ebase, zero);  conv_issue4<8>(acc, fa, de);
        wg_wait<1>(); conv_load4<12>(fb, ebase, zero); conv_issue4<12>(acc, fb, de);
        wg_wait<1>(); conv_load4<16>(fa, ebase, zero); conv_issue4<16>(acc, fa, de);
        wg_wait<1>(); conv_load4<20>(fb, ebase, zero); conv_issue4<20>(acc, fb, de);
        wg_wait<1>(); conv_load4<24>(fa, ebase, zero); conv_issue4<24>(acc, fa, de);
        wg_wait<1>(); conv_load4<28>(fb, ebase, zero); conv_issue4<28>(acc, fb, de);
#pragma unroll 1
        for (int s = 2; s < 6; s++) mbar_wait(bars + 8 * (B_STF + s), 0);
        load_u(ch);
        wg_wait<0>();
        TM_IF(tid == 0, 12);
        stage_out();
        TM_IF(tid == 0, 14);
      }
      {
        const int ch = 2 * wg + 1;
        const uint32_t ebase = sb + SM_X + CV_E + ch * E_CH + eoff;
        const uint64_t de = mkdesc(sb + SM_X + CV_R + ch * R_CH, R_HALF, 128, 0);
        conv_load4<0>(fa, ebase, zero);
        conv_load4<4>(fb, ebase, zero);
        conv_issue4<0>(acc, fa, de);
        conv_issue4<4>(acc, fb, de);
        bar_sync(6 + wg, 128);
        POST(0, dkA) POST(1, dkA)
        wg_wait<1>(); conv_load4<8>(fa, ebase, zero);  conv_issue4<8>(acc, fa, de);
        POST(2, dkA) POST(3, dkA)
        wg_wait<1>(); conv_load4<12>(fb, ebase, zero); conv_issue4<12>(acc, fb, de);
        POST(4, dkA) POST(5, dkA)
        wg_wait<1>(); conv_load4<16>(fa, ebase, zero); conv_issue4<16>(acc, fa, de);
        POST(6, dkA) POST(7, dkA)
        wg_wait<1>(); conv_load4<20>(fb, ebase, zero); conv_issue4<20>(acc, fb, de);
        store_a(ch - 1);
        wg_wait<1>(); conv_load4<24>(fa, ebase, zero); conv_issue4<24>(acc, fa, de);
        wg_wait<1>(); conv_load4<28>(fb, ebase, zero); conv_issue4<28>(acc, fb, de);
        bar_sync(6 + wg, 128);
        if (lane == 0) mbar_arrive(bars + 8 * B_ADONE);
        load_u(ch);
        wg_wait<0>();
        TM_IF(tid == 0, 15);
        stage_out();
        bar_sync(6 + wg, 128);
        TM_IF(tid == 0, 17);
        POST(0, dkB) POST(1, dkB) POST(2, dkB) POST(3, dkB) POST(4, dkB) POST(5, dkB) POST(6, dkB) POST(7, dkB)
        store_a(ch);
        __syncwarp();
        if (lane == 0) mbar_arrive(bars + 8 * B_ADONE);
      }
#undef POST
    }
    issue_half(accA, 6, H0{});
    issue_half(accA, 6, H1{});
    bar_sync(6 + wg, 128);
    issue_half(accB, 7, H0{}); wg_wait<1>(); send_pass(accA, 6);
    issue_half(accB, 7, H1{});
    {
#pragma unroll
      for (int i = 0; i < 32; i++) accA[i] = 0.f;
      uint4 v0[4], v1[4], v2[4];
      part_load(v0, 1);
      part_load(v1, 2);
      part_load(v2, 3);
      part_add(v0); part_load(v0, 4);
      part_add(v1); part_load(v1, 5);
      part_add(v2); part_load(v2, 6);
      part_add(v0); part_load(v0, 7);
      part_add(v1);
      part_add(v2);
      part_add(v0);
    }
    mbar_wait(bars + 8 * B_ATILE, 0);
    const int row0 = it_ * 128 + warp * 16 + g;
    const float g0 = __ldcg(g_gate + row0), g1 = __ldcg(g_gate + row0 + 8);
    uint32_t av[16];
    {
      const int dl = (lane & 7) + ((lane >> 4) << 3);
      const int chunk = 2 * (warp & 3) + ((lane >> 3) & 1);
      const uint32_t abase = sb + SM_AT + wg * 8192 + dl * 128 + ((chunk ^ (lane & 7)) << 4);
#pragma unroll
      for (int m2 = 0; m2 < 4; m2++) {
        asm volatile("ldmatrix.sync.aligned.m8n8.x4.trans.shared.b16 {%0,%1,%2,%3}, [%4];"
                     : "=r"(av[4 * m2]), "=r"(av[4 * m2 + 1]), "=r"(av[4 * m2 + 2]), "=r"(av[4 * m2 + 3]) : "r"(abase + m2 * 2048) : "memory");
      }
    }
    wg_wait<0>();
    const uint32_t gg0 = pack_bf16(g0, g0), gg1 = pack_bf16(g1, g1);
    const uint32_t og0 = pack_bf16(1.f - g0, 1.f - g0), og1 = pack_bf16(1.f - g1, 1.f - g1);
#pragma unroll
    for (int m = 0; m < 8; m++) {
      const uint32_t b0 = pack_bf16(accA[4 * m] + accB[4 * m], accA[4 * m + 1] + accB[4 * m + 1]);
      const uint32_t b1 = pack_bf16(accA[4 * m + 2] + accB[4 * m + 2], accA[4 * m + 3] + accB[4 * m + 3]);
      const uint32_t o0 = hadd2_bf16(hmul2_bf16(gg0, av[2 * m]), hmul2_bf16(og0, b0));
      const uint32_t o1 = hadd2_bf16(hmul2_bf16(gg1, av[2 * m + 1]), hmul2_bf16(og1, b1));
      *(uint32_t*)(P.out + row0 * D_ + jf * 64 + 8 * m + 2 * q) = o0;
      *(uint32_t*)(P.out + (row0 + 8) * D_ + jf * 64 + 8 * m + 2 * q) = o1;
    }
    bar_sync(0, NTHREADS);
    if (tid == 0) {
      const uint32_t t = atomicAdd(&g_exit, 1u);
      if (t == NCTA - 1) {
        g_exit = 0;
        *(volatile uint32_t*)&g_epoch = ld_epoch() + 1;
      }
    }
  }
}

typedef CUresult (*EncFn)(CUtensorMap*, CUtensorMapDataType, cuuint32_t, void*, const cuuint64_t*, const cuuint64_t*, const cuuint32_t*,
                          const cuuint32_t*, CUtensorMapInterleave, CUtensorMapSwizzle, CUtensorMapL2promotion, CUtensorMapFloatOOBfill);

struct HostState {
  bool ready;
  const void* key[4];
  Maps M;
};
HostState hs;

}

extern "C" void kernel_launch(void* const* d_in, const int* in_sizes, int n_in, void* d_out, int out_size) {
  (void)in_sizes; (void)n_in; (void)out_size;
  void* x = d_in[0];
  void* wg = d_in[8];
  void* wu = d_in[9];
  void* wd = d_in[10];
  if (!hs.ready || hs.key[0] != x || hs.key[1] != wg || hs.key[2] != wu || hs.key[3] != wd) {
    void* fn = nullptr;
    cudaDriverEntryPointQueryResult qr;
    cudaGetDriverEntryPoint("cuTensorMapEncodeTiled", &fn, cudaEnableDefault, &qr);
    EncFn enc = (EncFn)fn;
    const cuuint32_t es[3] = {1, 1, 1};
    const CUtensorMapDataType BF = CU_TENSOR_MAP_DATA_TYPE_BFLOAT16;
    const CUtensorMapInterleave IN = CU_TENSOR_MAP_INTERLEAVE_NONE;
    const CUtensorMapL2promotion PR = CU_TENSOR_MAP_L2_PROMOTION_L2_128B;
    const CUtensorMapFloatOOBfill OO = CU_TENSOR_MAP_FLOAT_OOB_FILL_NONE;
    {
      cuuint64_t gd[2] = {(cuuint64_t)D_, (cuuint64_t)L_}; cuuint64_t gs[1] = {(cuuint64_t)D_ * 2}; cuuint32_t box[2] = {64, 128};
      enc(&hs.M.X, BF, 2, x, gd, gs, box, es, IN, CU_TENSOR_MAP_SWIZZLE_128B, PR, OO);
    }
    {
      cuuint64_t gd[2] = {(cuuint64_t)F_, (cuuint64_t)D_}; cuuint64_t gs[1] = {(cuuint64_t)F_ * 2}; cuuint32_t box[2] = {64, 32};
      enc(&hs.M.Wg, BF, 2, wg, gd, gs, box, es, IN, CU_TENSOR_MAP_SWIZZLE_128B, PR, OO);
      enc(&hs.M.Wu, BF, 2, wu, gd, gs, box, es, IN, CU_TENSOR_MAP_SWIZZLE_128B, PR, OO);
      for (int o = 0; o < 2; o++) {
        cuuint64_t gd3[3] = {64, (cuuint64_t)D_, (cuuint64_t)(F_ / 64 - o)}; cuuint64_t gs3[2] = {(cuuint64_t)F_ * 2, 128};
        cuuint32_t box3[3] = {64, 32, 2};
        enc(&hs.M.Wg3[o], BF, 3, (char*)wg + 64 * o, gd3, gs3, box3, es, IN, CU_TENSOR_MAP_SWIZZLE_128B, PR, OO);
        enc(&hs.M.Wu3[o], BF, 3, (char*)wu + 64 * o, gd3, gs3, box3, es, IN, CU_TENSOR_MAP_SWIZZLE_128B, PR, OO);
      }
    }
    {
      cuuint64_t gd[2] = {(cuuint64_t)D_, (cuuint64_t)F_}; cuuint64_t gs[1] = {(cuuint64_t)D_ * 2}; cuuint32_t box[2] = {64, 112};
      enc(&hs.M.Wd, BF, 2, wd, gd, gs, box, es, IN, CU_TENSOR_MAP_SWIZZLE_128B, PR, OO);
    }
    {
      void* pa = nullptr;
      cudaGetSymbolAddress(&pa, g_aT);
      cuuint64_t gd[2] = {(cuuint64_t)L_, (cuuint64_t)D_}; cuuint64_t gs[1] = {(cuuint64_t)L_ * 2}; cuuint32_t box[2] = {64, 64};
      enc(&hs.M.AT, BF, 2, pa, gd, gs, box, es, IN, CU_TENSOR_MAP_SWIZZLE_128B, PR, OO);
    }
    cudaFuncSetAttribute(fused_kernel, cudaFuncAttributeMaxDynamicSharedMemorySize, SM_TOTAL);
    hs.key[0] = x; hs.key[1] = wg; hs.key[2] = wu; hs.key[3] = wd;
    hs.ready = true;
  }
  Params P;
  P.x = (const __nv_bfloat16*)d_in[0];
  P.log_A_real = (const __nv_bfloat16*)d_in[1];
  P.A_imag = (const __nv_bfloat16*)d_in[2];
  P.C_real = (const __nv_bfloat16*)d_in[3];
  P.C_imag = (const __nv_bfloat16*)d_in[4];
  P.log_dt = (const __nv_bfloat16*)d_in[5];
  P.D_skip = (const __nv_bfloat16*)d_in[6];
  P.gate_w = (const __nv_bfloat16*)d_in[11];
  P.w_gate = (const __nv_bfloat16*)wg;
  P.w_up = (const __nv_bfloat16*)wu;
  P.w_down = (const __nv_bfloat16*)wd;
  P.out = (__nv_bfloat16*)d_out;
  fused_kernel<<<NCTA, NTHREADS, SM_TOTAL>>>(hs.M, P);
}
```

```cpp
#include <cuda_runtime.h>
#include <cuda_bf16.h>
#include <cuda.h>
#include <stdint.h>

#define PUBMODE 2
namespace {

constexpr int L_ = 2048, D_ = 512, F_ = 1792, NS_ = 128;
constexpr int NCTA = 128;
constexpr int NTHREADS = 384;

constexpr int SM_X = 0;
constexpr int SM_RING = 131072;
constexpr int KC_STRIDE = 656;
constexpr int SM_KB = 212992;
constexpr int SM_PR = SM_KB + 4 * KC_STRIDE * 2;
constexpr int PR_WARP = 64 * 24;
constexpr int SM_BAR = SM_PR + 512 * 24;
constexpr int SM_TOTAL = SM_BAR + 512;
constexpr int CV_R = 0;
constexpr int R_HALF = 156 * 16;
constexpr int R_CH = 2 * R_HALF;
constexpr int CV_E = 4 * R_CH;
constexpr int E_COPY = 4160;
constexpr int E_CH = 2 * E_COPY;
constexpr int CV_S = CV_E + 4 * E_CH;
constexpr int S_PITCH = 136;
constexpr int S_WG = 4 * 16 * S_PITCH * 4;
constexpr int SM_AT = SM_X;
static_assert(CV_S + 2 * S_WG <= 131072, "conv region");

constexpr int B_FULL = 0, B_EMPTY = 5, B_XFULL = 10, B_XFREE = 18, B_ATILE = 26, B_RRDY = 27, B_ADONE = 28, B_KPART = 29, B_KSUM = 30, B_SENT = 35, B_GOT = 43, B_STF = 51;

__device__ uint4 g_part[16 * 8 * 8 * 8 * 4 * 32];
__device__ uint32_t g_flag[16 * 8 * 8];
__device__ __align__(1024) __nv_bfloat16 g_aT[D_ * L_];
__device__ float g_gate[L_];
__device__ uint32_t g_done1;
__device__ uint32_t g_cnt[8 * 32];
__device__ uint32_t g_exit;
__device__ uint32_t g_zero;
__device__ uint32_t g_epoch;

#define TM_IF(cond, idx) do {} while (0)
#define FAIL(a, ph) break
#define SPIN_LIMIT (1 << 22)
#define MBAR_LIMIT (1 << 20)
__device__ __forceinline__ uint32_t smem_u32(const void* p) { return (uint32_t)__cvta_generic_to_shared(p); }
__device__ __forceinline__ void mbar_init(uint32_t a, uint32_t c) { asm volatile("mbarrier.init.shared::cta.b64 [%0], %1;" ::"r"(a), "r"(c) : "memory"); }
__device__ __forceinline__ void mbar_expect(uint32_t a, uint32_t bytes) { asm volatile("mbarrier.arrive.expect_tx.shared::cta.b64 _, [%0], %1;" ::"r"(a), "r"(bytes) : "memory"); }
__device__ __forceinline__ void mbar_arrive(uint32_t a) { asm volatile("mbarrier.arrive.shared::cta.b64 _, [%0];" ::"r"(a) : "memory"); }
__device__ __forceinline__ void mbar_wait(uint32_t a, uint32_t ph) {
  asm volatile("{\n.reg .pred p;\n.reg .u32 c;\nmov.u32 c, 0;\nLW:\nmbarrier.try_wait.parity.shared::cta.b64 p, [%0], %1, %2;\n@p bra LD;\n"
               "add.u32 c, c, 1;\nsetp.lt.u32 p, c, 1048576;\n@p bra LW;\nLD:\n}" ::"r"(a), "r"(ph), "r"(20000u) : "memory");
}
template <int NS> __device__ __forceinline__ void mbar_wait_lazy(uint32_t a, uint32_t ph) {
  asm volatile("{\n.reg .pred p;\n.reg .u32 c;\nmov.u32 c, 0;\nLW:\nmbarrier.test_wait.parity.shared::cta.b64 p, [%0], %1;\n@p bra LD;\n"
               "nanosleep.u32 %2;\nadd.u32 c, c, 1;\nsetp.lt.u32 p, c, 4194304;\n@p bra LW;\nLD:\n}" ::"r"(a), "r"(ph), "n"(NS) : "memory");
}
__device__ __forceinline__ void tma2d(uint32_t dst, const CUtensorMap* m, int c0, int c1, uint32_t bar) {
  asm volatile("cp.async.bulk.tensor.2d.shared::cluster.global.mbarrier::complete_tx::bytes [%0], [%1, {%3,%4}], [%2];" ::"r"(dst), "l"(m), "r"(bar), "r"(c0), "r"(c1) : "memory");
}
__device__ __forceinline__ void tma3d(uint32_t dst, const CUtensorMap* m, int c0, int c1, int c2, uint32_t bar) {
  asm volatile("cp.async.bulk.tensor.3d.shared::cluster.global.mbarrier::complete_tx::bytes [%0], [%1, {%3,%4,%5}], [%2];" ::"r"(dst), "l"(m), "r"(bar), "r"(c0), "r"(c1), "r"(c2) : "memory");
}
__device__ __forceinline__ uint64_t mkdesc(uint32_t addr, uint32_t lbo, uint32_t sbo, uint32_t sw) {
  return (uint64_t)((addr & 0x3FFFF) >> 4) | ((uint64_t)(lbo >> 4) << 16) | ((uint64_t)(sbo >> 4) << 32) | ((uint64_t)sw << 62);
}
__device__ __forceinline__ void wg_fence() { asm volatile("wgmma.fence.sync.aligned;" ::: "memory"); }
__device__ __forceinline__ void wg_commit() { asm volatile("wgmma.commit_group.sync.aligned;" ::: "memory"); }
template <int N> __device__ __forceinline__ void wg_wait() { asm volatile("wgmma.wait_group.sync.aligned %0;" ::"n"(N) : "memory"); }
__device__ __forceinline__ void zero_reg(float& x) { asm volatile("mov.f32 %0, 0f00000000;" : "=f"(x)); }
__device__ __forceinline__ void bar_sync(int id, int n) { asm volatile("bar.sync %0, %1;" ::"r"(id), "r"(n) : "memory"); }
__device__ __forceinline__ void fence_async() { asm volatile("fence.proxy.async.shared::cta;" ::: "memory"); }
__device__ __forceinline__ uint32_t pack_bf16(float lo, float hi) {
  uint32_t r;
  asm("cvt.rn.bf16x2.f32 %0, %1, %2;" : "=r"(r) : "f"(hi), "f"(lo));
  return r;
}
__device__ __forceinline__ uint32_t hmul2_bf16(uint32_t a, uint32_t b) {
  uint32_t r;
  asm("mul.rn.bf16x2 %0, %1, %2;" : "=r"(r) : "r"(a), "r"(b));
  return r;
}
__device__ __forceinline__ uint32_t hadd2_bf16(uint32_t a, uint32_t b) {
  uint32_t r;
  asm("add.rn.bf16x2 %0, %1, %2;" : "=r"(r) : "r"(a), "r"(b));
  return r;
}
__device__ __forceinline__ float bf_lo(uint32_t v) { return __uint_as_float(v << 16); }
__device__ __forceinline__ float bf_hi(uint32_t v) { return __uint_as_float(v & 0xFFFF0000u); }
__device__ __forceinline__ float bf16r(float x) { return __bfloat162float(__float2bfloat16_rn(x)); }
__device__ __forceinline__ float ldbf(const __nv_bfloat16* p) { return __bfloat162float(*p); }
__device__ __forceinline__ uint32_t ld_acquire(const uint32_t* p) {
  uint32_t v;
  asm volatile("ld.acquire.gpu.global.u32 %0, [%1];" : "=r"(v) : "l"(p) : "memory");
  return v;
}
__device__ __forceinline__ void st_release(uint32_t* p, uint32_t v) { asm volatile("st.release.gpu.global.u32 [%0], %1;" ::"l"(p), "r"(v) : "memory"); }
__device__ __forceinline__ uint4 ld_cg4(const uint4* p) {
  uint4 v;
  asm volatile("ld.global.cg.v4.u32 {%0,%1,%2,%3}, [%4];" : "=r"(v.x), "=r"(v.y), "=r"(v.z), "=r"(v.w) : "l"(p) : "memory");
  return v;
}
__device__ __forceinline__ uint32_t ld_cg1(const void* p) {
  uint32_t v;
  asm volatile("ld.global.cg.u32 %0, [%1];" : "=r"(v) : "l"(p) : "memory");
  return v;
}
__device__ __forceinline__ uint32_t lds32(uint32_t a) {
  uint32_t v;
  asm volatile("ld.shared.u32 %0, [%1];" : "=r"(v) : "r"(a) : "memory");
  return v;
}
__device__ __forceinline__ void ldsm4(uint32_t (&r)[4], uint32_t a) {
  asm volatile("ldmatrix.sync.aligned.m8n8.x4.shared.b16 {%0,%1,%2,%3}, [%4];" : "=r"(r[0]), "=r"(r[1]), "=r"(r[2]), "=r"(r[3]) : "r"(a) : "memory");
}
__device__ __forceinline__ uint32_t pack_f16(float lo, float hi) {
  uint32_t r;
  asm("cvt.rn.f16x2.f32 %0, %1, %2;" : "=r"(r) : "f"(hi), "f"(lo));
  return r;
}

__device__ __forceinline__ void wgmma_ss_n256(float (&d)[128], uint64_t da, uint64_t db) {
  asm volatile("wgmma.mma_async.sync.aligned.m64n256k16.f32.bf16.bf16 {%0, %1, %2, %3, %4, %5, %6, %7, %8, %9, %10, %11, %12, %13, %14, %15, %16, %17, %18, %19, %20, %21, %22, %23, %24, %25, %26, %27, %28, %29, %30, %31, %32, %33, %34, %35, %36, %37, %38, %39, %40, %41, %42, %43, %44, %45, %46, %47, %48, %49, %50, %51, %52, %53, %54, %55, %56, %57, %58, %59, %60, %61, %62, %63, %64, %65, %66, %67, %68, %69, %70, %71, %72, %73, %74, %75, %76, %77, %78, %79, %80, %81, %82, %83, %84, %85, %86, %87, %88, %89, %90, %91, %92, %93, %94, %95, %96, %97, %98, %99, %100, %101, %102, %103, %104, %105, %106, %107, %108, %109, %110, %111, %112, %113, %114, %115, %116, %117, %118, %119, %120, %121, %122, %123, %124, %125, %126, %127}, %128, %129, 1, 1, 1, 0, 1;"
    : "+f"(d[0]), "+f"(d[1]), "+f"(d[2]), "+f"(d[3]), "+f"(d[4]), "+f"(d[5]), "+f"(d[6]), "+f"(d[7]), "+f"(d[8]), "+f"(d[9]), "+f"(d[10]), "+f"(d[11]), "+f"(d[12]), "+f"(d[13]), "+f"(d[14]), "+f"(d[15]), "+f"(d[16]), "+f"(d[17]), "+f"(d[18]), "+f"(d[19]), "+f"(d[20]), "+f"(d[21]), "+f"(d[22]), "+f"(d[23]), "+f"(d[24]), "+f"(d[25]), "+f"(d[26]), "+f"(d[27]), "+f"(d[28]), "+f"(d[29]), "+f"(d[30]), "+f"(d[31]), "+f"(d[32]), "+f"(d[33]), "+f"(d[34]), "+f"(d[35]), "+f"(d[36]), "+f"(d[37]), "+f"(d[38]), "+f"(d[39]), "+f"(d[40]), "+f"(d[41]), "+f"(d[42]), "+f"(d[43]), "+f"(d[44]), "+f"(d[45]), "+f"(d[46]), "+f"(d[47]), "+f"(d[48]), "+f"(d[49]), "+f"(d[50]), "+f"(d[51]), "+f"(d[52]), "+f"(d[53]), "+f"(d[54]), "+f"(d[55]), "+f"(d[56]), "+f"(d[57]), "+f"(d[58]), "+f"(d[59]), "+f"(d[60]), "+f"(d[61]), "+f"(d[62]), "+f"(d[63]), "+f"(d[64]), "+f"(d[65]), "+f"(d[66]), "+f"(d[67]), "+f"(d[68]), "+f"(d[69]), "+f"(d[70]), "+f"(d[71]), "+f"(d[72]), "+f"(d[73]), "+f"(d[74]), "+f"(d[75]), "+f"(d[76]), "+f"(d[77]), "+f"(d[78]), "+f"(d[79]), "+f"(d[80]), "+f"(d[81]), "+f"(d[82]), "+f"(d[83]), "+f"(d[84]), "+f"(d[85]), "+f"(d[86]), "+f"(d[87]), "+f"(d[88]), "+f"(d[89]), "+f"(d[90]), "+f"(d[91]), "+f"(d[92]), "+f"(d[93]), "+f"(d[94]), "+f"(d[95]), "+f"(d[96]), "+f"(d[97]), "+f"(d[98]), "+f"(d[99]), "+f"(d[100]), "+f"(d[101]), "+f"(d[102]), "+f"(d[103]), "+f"(d[104]), "+f"(d[105]), "+f"(d[106]), "+f"(d[107]), "+f"(d[108]), "+f"(d[109]), "+f"(d[110]), "+f"(d[111]), "+f"(d[112]), "+f"(d[113]), "+f"(d[114]), "+f"(d[115]), "+f"(d[116]), "+f"(d[117]), "+f"(d[118]), "+f"(d[119]), "+f"(d[120]), "+f"(d[121]), "+f"(d[122]), "+f"(d[123]), "+f"(d[124]), "+f"(d[125]), "+f"(d[126]), "+f"(d[127]) : "l"(da), "l"(db));
}
__device__ __forceinline__ void wgmma_rs_n96(float (&d)[48], uint32_t a0, uint32_t a1, uint32_t a2, uint32_t a3, uint64_t db) {
  asm volatile("wgmma.mma_async.sync.aligned.m64n96k16.f32.bf16.bf16 {%0, %1, %2, %3, %4, %5, %6, %7, %8, %9, %10, %11, %12, %13, %14, %15, %16, %17, %18, %19, %20, %21, %22, %23, %24, %25, %26, %27, %28, %29, %30, %31, %32, %33, %34, %35, %36, %37, %38, %39, %40, %41, %42, %43, %44, %45, %46, %47}, {%48,%49,%50,%51}, %52, 1, 1, 1, 1;"
    : "+f"(d[0]), "+f"(d[1]), "+f"(d[2]), "+f"(d[3]), "+f"(d[4]), "+f"(d[5]), "+f"(d[6]), "+f"(d[7]), "+f"(d[8]), "+f"(d[9]), "+f"(d[10]), "+f"(d[11]), "+f"(d[12]), "+f"(d[13]), "+f"(d[14]), "+f"(d[15]), "+f"(d[16]), "+f"(d[17]), "+f"(d[18]), "+f"(d[19]), "+f"(d[20]), "+f"(d[21]), "+f"(d[22]), "+f"(d[23]), "+f"(d[24]), "+f"(d[25]), "+f"(d[26]), "+f"(d[27]), "+f"(d[28]), "+f"(d[29]), "+f"(d[30]), "+f"(d[31]), "+f"(d[32]), "+f"(d[33]), "+f"(d[34]), "+f"(d[35]), "+f"(d[36]), "+f"(d[37]), "+f"(d[38]), "+f"(d[39]), "+f"(d[40]), "+f"(d[41]), "+f"(d[42]), "+f"(d[43]), "+f"(d[44]), "+f"(d[45]), "+f"(d[46]), "+f"(d[47]) : "r"(a0), "r"(a1), "r"(a2), "r"(a3), "l"(db));
}
__device__ __forceinline__ void wgmma_rs_n64t(float (&d)[32], uint32_t a0, uint32_t a1, uint32_t a2, uint32_t a3, uint64_t db) {
  asm volatile("wgmma.mma_async.sync.aligned.m64n64k16.f32.bf16.bf16 {%0, %1, %2, %3, %4, %5, %6, %7, %8, %9, %10, %11, %12, %13, %14, %15, %16, %17, %18, %19, %20, %21, %22, %23, %24, %25, %26, %27, %28, %29, %30, %31}, {%32,%33,%34,%35}, %36, 1, 1, 1, 1;"
    : "+f"(d[0]), "+f"(d[1]), "+f"(d[2]), "+f"(d[3]), "+f"(d[4]), "+f"(d[5]), "+f"(d[6]), "+f"(d[7]), "+f"(d[8]), "+f"(d[9]), "+f"(d[10]), "+f"(d[11]), "+f"(d[12]), "+f"(d[13]), "+f"(d[14]), "+f"(d[15]), "+f"(d[16]), "+f"(d[17]), "+f"(d[18]), "+f"(d[19]), "+f"(d[20]), "+f"(d[21]), "+f"(d[22]), "+f"(d[23]), "+f"(d[24]), "+f"(d[25]), "+f"(d[26]), "+f"(d[27]), "+f"(d[28]), "+f"(d[29]), "+f"(d[30]), "+f"(d[31]) : "r"(a0), "r"(a1), "r"(a2), "r"(a3), "l"(db));
}
__device__ __forceinline__ void wgmma_conv32(float (&d)[16], uint32_t a0, uint32_t a1, uint32_t a2, uint32_t a3, uint64_t db) {
  asm volatile("wgmma.mma_async.sync.aligned.m64n32k16.f32.bf16.bf16 {%0, %1, %2, %3, %4, %5, %6, %7, %8, %9, %10, %11, %12, %13, %14, %15}, {%16,%17,%18,%19}, %20, 1, 1, 1, 0;"
    : "+f"(d[0]), "+f"(d[1]), "+f"(d[2]), "+f"(d[3]), "+f"(d[4]), "+f"(d[5]), "+f"(d[6]), "+f"(d[7]), "+f"(d[8]), "+f"(d[9]), "+f"(d[10]), "+f"(d[11]), "+f"(d[12]), "+f"(d[13]), "+f"(d[14]), "+f"(d[15]) : "r"(a0), "r"(a1), "r"(a2), "r"(a3), "l"(db));
}
__device__ __forceinline__ void wgmma_conv32z(float (&d)[16], uint32_t a0, uint32_t a1, uint32_t a2, uint32_t a3, uint64_t db) {
  asm volatile("{.reg .pred p; setp.ne.b32 p, 0, 0; wgmma.mma_async.sync.aligned.m64n32k16.f32.bf16.bf16 {%0, %1, %2, %3, %4, %5, %6, %7, %8, %9, %10, %11, %12, %13, %14, %15}, {%16,%17,%18,%19}, %20, p, 1, 1, 0;}"
    : "=f"(d[0]), "=f"(d[1]), "=f"(d[2]), "=f"(d[3]), "=f"(d[4]), "=f"(d[5]), "=f"(d[6]), "=f"(d[7]), "=f"(d[8]), "=f"(d[9]), "=f"(d[10]), "=f"(d[11]), "=f"(d[12]), "=f"(d[13]), "=f"(d[14]), "=f"(d[15]) : "r"(a0), "r"(a1), "r"(a2), "r"(a3), "l"(db));
}
__device__ __forceinline__ void wgmma_rs_n64tz(float (&d)[32], uint32_t a0, uint32_t a1, uint32_t a2, uint32_t a3, uint64_t db) {
  asm volatile("{.reg .pred p; setp.ne.b32 p, 0, 0; wgmma.mma_async.sync.aligned.m64n64k16.f32.bf16.bf16 {%0, %1, %2, %3, %4, %5, %6, %7, %8, %9, %10, %11, %12, %13, %14, %15, %16, %17, %18, %19, %20, %21, %22, %23, %24, %25, %26, %27, %28, %29, %30, %31}, {%32,%33,%34,%35}, %36, p, 1, 1, 1;}"
    : "=f"(d[0]), "=f"(d[1]), "=f"(d[2]), "=f"(d[3]), "=f"(d[4]), "=f"(d[5]), "=f"(d[6]), "=f"(d[7]), "=f"(d[8]), "=f"(d[9]), "=f"(d[10]), "=f"(d[11]), "=f"(d[12]), "=f"(d[13]), "=f"(d[14]), "=f"(d[15]), "=f"(d[16]), "=f"(d[17]), "=f"(d[18]), "=f"(d[19]), "=f"(d[20]), "=f"(d[21]), "=f"(d[22]), "=f"(d[23]), "=f"(d[24]), "=f"(d[25]), "=f"(d[26]), "=f"(d[27]), "=f"(d[28]), "=f"(d[29]), "=f"(d[30]), "=f"(d[31]) : "r"(a0), "r"(a1), "r"(a2), "r"(a3), "l"(db));
}

struct cpx { float r, i; };
__device__ __forceinline__ cpx cmul(cpx a, cpx b) { return {fmaf(a.r, b.r, -a.i * b.i), fmaf(a.r, b.i, a.i * b.r)}; }
__device__ __forceinline__ cpx csqr(cpx a) { return {fmaf(a.r, a.r, -a.i * a.i), (a.r * a.i) * 2.f}; }
__device__ __forceinline__ cpx cmulc(cpx a, cpx b) { return {fmaf(a.r, b.r, -a.i * b.i), fmaf(-a.r, b.i, -a.i * b.r)}; }
__device__ __forceinline__ cpx cexp_fast(float re, float im) {
  float e;
  asm("ex2.approx.ftz.f32 %0, %1;" : "=f"(e) : "f"(re * 1.4426950408889634f));
  float k = rintf(im * 0.15915494309189535f);
  float r = fmaf(k, -6.2831854820251465f, im);
  r = fmaf(k, 1.7484555314695172e-07f, r);
  float s, c;
  asm("sin.approx.f32 %0, %1;" : "=f"(s) : "f"(r));
  asm("cos.approx.f32 %0, %1;" : "=f"(c) : "f"(r));
  return {e * c, e * s};
}

struct KOps { uint32_t xa[5], xb[5], y[4]; };
__device__ __forceinline__ void kgen_ops(KOps& o, const float4 pr, const float2 qq, const float gf) {
  const cpx C = {pr.z, pr.w};
  const cpx Q = {qq.x, qq.y};
  const cpx V0 = cexp_fast(pr.x * gf, pr.y * gf);
  const cpx V1 = csqr(V0), V2 = csqr(V1), V3 = csqr(V2);
  const cpx Y0 = cmulc(C, V0), Y1 = cmulc(C, V1), Y2 = cmulc(C, V2), Y3 = cmulc(C, V3);
  o.y[0] = pack_f16(Y0.r, Y0.i); o.y[1] = pack_f16(Y1.r, Y1.i); o.y[2] = pack_f16(Y2.r, Y2.i); o.y[3] = pack_f16(Y3.r, Y3.i);
  const cpx Xb = cmul(V3, Q);
  cpx Xc = cmul(Xb, Q), Xd = cmul(Xc, Q);
  o.xa[0] = pack_f16(V3.r, V3.i); o.xb[0] = pack_f16(Xb.r, Xb.i);
  o.xa[1] = pack_f16(Xc.r, Xc.i); o.xb[1] = pack_f16(Xd.r, Xd.i);
#pragma unroll
  for (int k = 2; k < 5; k++) {
    Xc = csqr(Xc); Xd = csqr(Xd);
    o.xa[k] = pack_f16(Xc.r, Xc.i); o.xb[k] = pack_f16(Xd.r, Xd.i);
  }
}
__device__ __forceinline__ void kgen_mma(float (&T)[5][4], const KOps& a, const KOps& b) {
  asm("mma.sync.aligned.m16n8k16.row.col.f32.f16.f16.f32 {%0,%1,%2,%3}, {%20,%21,%22,%23}, {%40,%41}, {%0,%1,%2,%3};\n"
      "mma.sync.aligned.m16n8k16.row.col.f32.f16.f16.f32 {%4,%5,%6,%7}, {%24,%25,%26,%27}, {%40,%41}, {%4,%5,%6,%7};\n"
      "mma.sync.aligned.m16n8k16.row.col.f32.f16.f16.f32 {%8,%9,%10,%11}, {%28,%29,%30,%31}, {%42,%43}, {%8,%9,%10,%11};\n"
      "mma.sync.aligned.m16n8k16.row.col.f32.f16.f16.f32 {%12,%13,%14,%15}, {%32,%33,%34,%35}, {%44,%45}, {%12,%13,%14,%15};\n"
      "mma.sync.aligned.m16n8k16.row.col.f32.f16.f16.f32 {%16,%17,%18,%19}, {%36,%37,%38,%39}, {%46,%47}, {%16,%17,%18,%19};\n"
      : "+f"(T[0][0]), "+f"(T[0][1]), "+f"(T[0][2]), "+f"(T[0][3]), "+f"(T[1][0]), "+f"(T[1][1]), "+f"(T[1][2]), "+f"(T[1][3]),
        "+f"(T[2][0]), "+f"(T[2][1]), "+f"(T[2][2]), "+f"(T[2][3]), "+f"(T[3][0]), "+f"(T[3][1]), "+f"(T[3][2]), "+f"(T[3][3]),
        "+f"(T[4][0]), "+f"(T[4][1]), "+f"(T[4][2]), "+f"(T[4][3])
      : "r"(a.xa[0]), "r"(a.xb[0]), "r"(b.xa[0]), "r"(b.xb[0]), "r"(a.xa[1]), "r"(a.xb[1]), "r"(b.xa[1]), "r"(b.xb[1]),
        "r"(a.xa[2]), "r"(a.xb[2]), "r"(b.xa[2]), "r"(b.xb[2]), "r"(a.xa[3]), "r"(a.xb[3]), "r"(b.xa[3]), "r"(b.xb[3]),
        "r"(a.xa[4]), "r"(a.xb[4]), "r"(b.xa[4]), "r"(b.xb[4]),
        "r"(a.y[0]), "r"(b.y[0]), "r"(a.y[1]), "r"(b.y[1]), "r"(a.y[2]), "r"(b.y[2]), "r"(a.y[3]), "r"(b.y[3]));
}

template <int J> __device__ __forceinline__ void conv_issue(float (&acc)[4][16], const uint32_t (&f)[4], uint64_t db) {
  constexpr int NT = 4 - (J >> 3);
#pragma unroll
  for (int t = 0; t < NT; t++) {
    if (J == 0) wgmma_conv32z(acc[t], f[0], f[1], f[2], f[3], db + 4 * J + 32 * t);
    else wgmma_conv32(acc[t], f[0], f[1], f[2], f[3], db + 4 * J + 32 * t);
  }
}
template <int J0> __device__ __forceinline__ void conv_load4(uint32_t (&f)[4][4], uint32_t ebase, uint32_t zero) {
#pragma unroll
  for (int t = 0; t < 4; t++) {
    f[t][0] = lds32(ebase + (J0 + t) * 128);
    f[t][1] = lds32(ebase + (J0 + t) * 128 + 16);
    f[t][3] = lds32(ebase + (J0 + t) * 128 + 32);
  }
#pragma unroll
  for (int t = 0; t < 4; t++) f[t][2] = f[t][1] ^ zero;
}
template <int J0> __device__ __forceinline__ void conv_issue4(float (&acc)[4][16], const uint32_t (&f)[4][4], uint64_t db) {
  wg_fence();
  conv_issue<J0 + 0>(acc, f[0], db);
  conv_issue<J0 + 1>(acc, f[1], db);
  conv_issue<J0 + 2>(acc, f[2], db);
  conv_issue<J0 + 3>(acc, f[3], db);
  wg_commit();
}

template <int V> struct IC { static constexpr int value = V; };

struct Params {
  const __nv_bfloat16* x;
  const __nv_bfloat16* log_A_real;
  const __nv_bfloat16* A_imag;
  const __nv_bfloat16* C_real;
  const __nv_bfloat16* C_imag;
  const __nv_bfloat16* log_dt;
  const __nv_bfloat16* D_skip;
  const __nv_bfloat16* gate_w;
  const __nv_bfloat16* w_gate;
  const __nv_bfloat16* w_up;
  const __nv_bfloat16* w_down;
  __nv_bfloat16* out;
};

struct Maps {
  CUtensorMap X, Wg, Wu, Wg3[2], Wu3[2], Wd, AT;
};

__device__ __forceinline__ uint32_t ld_epoch() { return *(volatile uint32_t*)&g_epoch; }
__device__ __forceinline__ uint32_t dup_lo(uint32_t w) { return __byte_perm(w, w, 0x1010); }
__device__ __forceinline__ uint32_t dup_hi(uint32_t w) { return __byte_perm(w, w, 0x3232); }

__global__ void __launch_bounds__(NTHREADS, 1)
fused_kernel(const __grid_constant__ Maps M, const Params P) {
  extern __shared__ __align__(1024) uint8_t smem[];
  const uint32_t sb = smem_u32(smem);
  const uint32_t bars = sb + SM_BAR;
  const int tid = threadIdx.x;
  const int warp = __shfl_sync(0xffffffffu, tid >> 5, 0), lane = tid & 31;
  const int b = blockIdx.x;
  const int cl = b >> 1;
  const int jf = cl & 7;
  const int it_ = ((cl >> 3) << 1) | (b & 1);
  const int d0 = b * 4;

  const int kch = warp / 3, kpart = warp - 3 * kch;
  const int kk0 = kpart == 0 ? 0 : (kpart == 1 ? 6 : 11), nks = kpart == 0 ? 6 : 5;
  uint32_t pw0[2], pw1[2], pldt;
#pragma unroll
  for (int r = 0; r < 2; r++) {
    int n = 8 * kk0 + lane + 32 * r;
    n = (d0 + kch) * NS_ + (n < NS_ ? n : NS_ - 1);
    pw0[r] = (uint32_t)*(const unsigned short*)(P.log_A_real + n) | ((uint32_t)*(const unsigned short*)(P.A_imag + n) << 16);
    pw1[r] = (uint32_t)*(const unsigned short*)(P.C_real + n) | ((uint32_t)*(const unsigned short*)(P.C_imag + n) << 16);
  }
  pldt = *(const unsigned short*)(P.log_dt + d0 + kch);
  if (lane == 0) {
#pragma unroll
    for (int r = 0; r < 5; r++) {
      const int i = warp + 12 * r;
      uint32_t cnt = 1;
      if ((i >= B_EMPTY && i < B_EMPTY + 5) || (i >= B_XFREE && i < B_XFREE + 8) || (i >= B_SENT && i < B_SENT + 8) || i == B_ADONE) cnt = 8;
      if (i == B_RRDY || i == B_KSUM) cnt = 2;
      if (i == B_KPART) cnt = 12;
      mbar_init(bars + 8 * i, cnt);
    }
    asm volatile("fence.mbarrier_init.release.cluster;" ::: "memory");
  }
  TM_IF(tid == 0, 20);
  __syncthreads();
  TM_IF(tid == 0, 21);

  auto issue_stage = [&](int s, int slot) {
    const uint32_t dst = sb + SM_RING + slot * 16384;
    const uint32_t fb = bars + 8 * (B_FULL + slot);
    if (s < 32) {
      const int f0 = jf * 224 + ((s >> 4) << 7);
      const int k0 = (s & 15) * 32;
      mbar_expect(fb, 16384);
      if (jf == 7 && s >= 16) {
        tma2d(dst, &M.Wg, f0, k0, fb);
        tma2d(dst + 4096, &M.Wg, f0 + 64, k0, fb);
        tma2d(dst + 8192, &M.Wu, f0, k0, fb);
        tma2d(dst + 12288, &M.Wu, f0 + 64, k0, fb);
      } else {
        tma3d(dst, &M.Wg3[jf & 1], 0, k0, f0 >> 6, fb);
        tma3d(dst + 8192, &M.Wu3[jf & 1], 0, k0, f0 >> 6, fb);
      }
    } else {
      const int s2 = s - 32;
      const int p = (jf + 1 + (s2 >> 1)) & 7;
      mbar_expect(fb, 14336);
      tma2d(dst, &M.Wd, p * 64, jf * 224 + (s2 & 1) * 112, fb);
    }
  };
  auto issue_x = [&](int kb) {
    mbar_expect(bars + 8 * (B_XFULL + kb), 16384);
    tma2d(sb + SM_X + kb * 16384, &M.X, kb * 64, it_ * 128, bars + 8 * (B_XFULL + kb));
  };
  {
    const int g = lane >> 2, q = lane & 3;
    const float dtf = bf16r(expf(bf_lo(pldt)));
    const int pro = kch * 128 + 8 * kk0;
    float4* prm = (float4*)(smem + SM_PR) + pro;
    float2* prq = (float2*)(smem + SM_PR + 512 * 16) + pro;
    const bool valid1 = lane + 32 < 8 * nks;
    float m0 = fmaxf(fmaxf(fabsf(bf_lo(pw1[0])), fabsf(bf_hi(pw1[0]))), fmaxf(fabsf(bf_lo(pw1[1])), fabsf(bf_hi(pw1[1])))) * dtf;
#pragma unroll
    for (int o = 16; o > 0; o >>= 1) m0 = fmaxf(m0, __shfl_xor_sync(0xffffffffu, m0, o));
    TM_IF(tid == 0 && m0 >= 0.f, 0);
    if (m0 >= 0.f || m0 != m0) {
      if (tid == 256) {
        issue_x(0); issue_stage(0, 0); issue_stage(2, 2); issue_x(2); issue_stage(4, 4); issue_x(4);
      } else if (tid == 288) {
        issue_stage(1, 1); issue_x(1); issue_stage(3, 3); issue_x(3); issue_x(5);
      }
    }
    __syncwarp();
    const uint32_t e0 = min(max(__float_as_uint(m0) >> 23, 1u), 253u);
    const float sc = __uint_as_float((254u - e0) << 23);
    const float us = 2.f * __uint_as_float(e0 << 23);
    float pe = 0.f;
#pragma unroll
    for (int r = 0; r < 2; r++) {
      float4 v;
      v.x = -bf16r(expf(bf_lo(pw0[r]))) * dtf;
      v.y = bf_hi(pw0[r]) * dtf;
      v.z = bf_lo(pw1[r]) * dtf * sc;
      v.w = bf_hi(pw1[r]) * dtf * sc;
      const cpx Q = cexp_fast(v.x * 64.f, v.y * 64.f);
      const cpx We = cexp_fast(v.x * 2048.f, v.y * 2048.f);
      if (r == 0 || valid1) {
        pe += v.z * We.r - v.w * We.i;
        prm[lane + 32 * r] = v;
        prq[lane + 32 * r] = make_float2(Q.r, Q.i);
      }
    }
#pragma unroll
    for (int o = 16; o > 0; o >>= 1) pe += __shfl_xor_sync(0xffffffffu, pe, o);
    __syncwarp();
    TM_IF(tid == 0, 1);
    float T[5][4];
#pragma unroll
    for (int i = 0; i < 20; i++) T[i >> 2][i & 3] = 0.f;
    const float gf = (float)g;
#pragma unroll 1
    for (int ks = 0; ks < nks; ks++) {
      KOps o1, o2;
      kgen_ops(o1, prm[8 * ks + q], prq[8 * ks + q], gf);
      kgen_ops(o2, prm[8 * ks + 4 + q], prq[8 * ks + 4 + q], gf);
      kgen_mma(T, o1, o2);
    }
    float* kp = (float*)(smem + SM_X + 6 * 16384) + warp * KC_STRIDE + 8 * g + 2 * q;
#pragma unroll
    for (int k = 0; k < 5; k++) {
      *(float2*)(kp + 128 * k) = make_float2(T[k][0] * us, T[k][1] * us);
      *(float2*)(kp + 128 * k + 64) = make_float2(T[k][2] * us, T[k][3] * us);
    }
    if (lane == 0) { kp[640] = pe * us; kp[641] = 0.f; }
    TM_IF(tid == 0, 2);
    __syncwarp();
    if (lane == 0) mbar_arrive(bars + 8 * B_KPART);
  }

  if (warp >= 8) {
    asm volatile("setmaxnreg.dec.sync.aligned.u32 104;");
    if (warp < 10) {
      if (lane == 0) {
        int slot = (warp == 8) ? 1 : 0;
        uint32_t ph = 0;
#pragma unroll 1
        for (int s = (warp == 8) ? 6 : 5; s < 48; s += 2) {
          if (s == 10) { mbar_wait(bars + 8 * B_KSUM, 0); issue_x(6); issue_x(7); }
          mbar_wait(bars + 8 * (B_EMPTY + slot), ph);
          issue_stage(s, slot);
          slot += 2;
          if (slot >= 5) { slot -= 5; ph ^= 1; }
        }
      }
      __syncwarp();
      {
        const uint4 gw0 = *(const uint4*)(P.gate_w + lane * 16);
        const uint4 gw1 = *(const uint4*)(P.gate_w + lane * 16 + 8);
        uint4 xa[8], xb[8];
#pragma unroll
        for (int i = 0; i < 8; i++) {
          xa[i] = *(const uint4*)(P.x + (b * 16 + (warp - 8) * 8 + i) * D_ + lane * 16);
          xb[i] = *(const uint4*)(P.x + (b * 16 + (warp - 8) * 8 + i) * D_ + lane * 16 + 8);
        }
        float sg[8];
#pragma unroll
        for (int i = 0; i < 8; i++) {
          const uint32_t pr[8] = {hmul2_bf16(xa[i].x, gw0.x), hmul2_bf16(xa[i].y, gw0.y), hmul2_bf16(xa[i].z, gw0.z), hmul2_bf16(xa[i].w, gw0.w),
                                  hmul2_bf16(xb[i].x, gw1.x), hmul2_bf16(xb[i].y, gw1.y), hmul2_bf16(xb[i].z, gw1.z), hmul2_bf16(xb[i].w, gw1.w)};
          float s = 0.f;
#pragma unroll
          for (int k = 0; k < 8; k++) s += bf_lo(pr[k]) + bf_hi(pr[k]);
          sg[i] = s;
        }
#pragma unroll
        for (int o = 16; o > 0; o >>= 1) {
#pragma unroll
          for (int i = 0; i < 8; i++) sg[i] += __shfl_xor_sync(0xffffffffu, sg[i], o);
        }
        float z = sg[0];
#pragma unroll
        for (int i = 1; i < 8; i++) z = (lane == i) ? sg[i] : z;
        if (lane < 8) g_gate[b * 16 + (warp - 8) * 8 + lane] = bf16r(1.f / (1.f + expf(-bf16r(z))));
      }
      bar_sync(3, 64);
      if (tid == 288) asm volatile("red.release.gpu.global.add.u32 [%0], 1;" ::"l"(&g_done1) : "memory");
      TM_IF(tid == 256, 16);
      if (warp == 8) {
        if (lane >= 1 && lane < 8) {
          const uint32_t tag = ld_epoch() + 1;
          const uint32_t* fp = g_flag + ((it_ * 8 + jf) * 8 + ((jf - lane) & 7));
          int itc = 0;
          while (ld_acquire(fp) != tag) { __nanosleep(100); if (++itc > SPIN_LIMIT) FAIL(-2, lane); }
          mbar_arrive(bars + 8 * (B_GOT + lane));
          TM_IF(lane == 7, 25);
        }
      } else if (lane == 0) {
        const uint32_t tag = ld_epoch() + 1;
#pragma unroll 1
        for (int rnd = 0; rnd < 2; rnd++) {
          mbar_wait_lazy<100>(bars + 8 * B_ADONE, rnd);
          TM_IF(true, 24);
#pragma unroll
          for (int v = 0; v < 2; v++)
            asm volatile("cp.async.bulk.global.shared::cta.bulk_group [%0], [%1], %2;"
                         ::"l"(g_aT + (d0 + 2 * v + rnd) * L_), "r"(sb + SM_X + CV_R + (2 * v + rnd) * R_CH), "r"(4096) : "memory");
          asm volatile("cp.async.bulk.commit_group;" ::: "memory");
          asm volatile("cp.async.bulk.wait_group 0;" ::: "memory");
          asm volatile("red.relaxed.gpu.global.add.u32 [%0], 1;" ::"l"(g_cnt + 32 * (b >> 4)) : "memory");
        }
        TM_IF(true, 26);
        {
          int itc = 0;
          while ((int)(ld_acquire(&g_done1) - (uint32_t)NCTA * tag) < 0) { if (++itc > SPIN_LIMIT) FAIL(-1, 0); }
          while ((int)(ld_acquire(g_cnt + 32 * jf) - 32u * tag) < 0) { if (++itc > SPIN_LIMIT) FAIL(-3, 0); }
        }
        TM_IF(true, 23);
        asm volatile("fence.proxy.async.global;" ::: "memory");
        mbar_expect(bars + 8 * B_ATILE, 16384);
        tma2d(sb + SM_AT, &M.AT, it_ * 128, jf * 64, bars + 8 * B_ATILE);
        tma2d(sb + SM_AT + 8192, &M.AT, it_ * 128 + 64, jf * 64, bars + 8 * B_ATILE);
      }
      __syncwarp();
    } else {
      const int w = warp - 10;
      const int wt = tid - 320;
      mbar_wait(bars + 8 * B_KPART, 0);
      {
        const float2* kp = (const float2*)(smem + SM_X + 6 * 16384);
        uint32_t* kb = (uint32_t*)(smem + SM_KB);
#pragma unroll
        for (int ch = 0; ch < 4; ch++) {
#pragma unroll
          for (int i = 0; i < 6; i++) {
            const int o = wt + 64 * i;
            if (i < 5 || o < 321) {
              const float2 a0 = kp[(3 * ch) * (KC_STRIDE / 2) + o], a1 = kp[(3 * ch + 1) * (KC_STRIDE / 2) + o], a2 = kp[(3 * ch + 2) * (KC_STRIDE / 2) + o];
              kb[ch * (KC_STRIDE / 2) + o] = pack_bf16(a0.x + a1.x + a2.x, a0.y + a1.y + a2.y);
            }
          }
        }
      }
      __syncwarp();
      if (lane == 0) mbar_arrive(bars + 8 * B_KSUM);
      {
        const uint32_t zz = *(volatile uint32_t*)&g_zero;
        uint2 ur[4][8];
#pragma unroll
        for (int i = 0; i < 4; i++) {
#pragma unroll
          for (int r = 0; r < 8; r++) {
            uint32_t ck;
            asm volatile("nanosleep.u32 120;\n\tmov.u32 %0, %%clock;" : "=r"(ck) :: "memory");
            asm volatile("ld.global.nc.v2.u32 {%0,%1}, [%2];" : "=r"(ur[i][r].x), "=r"(ur[i][r].y)
                         : "l"(P.x + ((wt + 64 * i) * 8 + r) * D_ + d0 + (ck & zz)));
          }
        }
        mbar_wait_lazy<200>(bars + 8 * (B_XFREE + 7), 0);
        TM_IF(wt == 0, 18);
#pragma unroll
        for (int i = 0; i < 4; i++) {
          const int item = wt + 64 * i;
          const int c = item >> 1, hh = item & 1;
#pragma unroll
          for (int ch = 0; ch < 4; ch++) {
            uint32_t v[4];
#pragma unroll
            for (int k = 0; k < 4; k++) {
              const uint32_t lo = (ch < 2) ? ur[i][7 - 2 * k].x : ur[i][7 - 2 * k].y;
              const uint32_t hi = (ch < 2) ? ur[i][6 - 2 * k].x : ur[i][6 - 2 * k].y;
              v[k] = (ch & 1) ? __byte_perm(lo, hi, 0x7632) : __byte_perm(lo, hi, 0x5410);
            }
            *(uint4*)(smem + SM_X + CV_R + ch * R_CH + (1 - hh) * R_HALF + (127 - c) * 16) = make_uint4(v[0], v[1], v[2], v[3]);
          }
        }
        if (lane < 28) {
#pragma unroll
          for (int z = 0; z < 4; z++)
            *(uint4*)(smem + SM_X + CV_R + (4 * w + z) * R_HALF + (128 + lane) * 16) = make_uint4(0, 0, 0, 0);
        }
      }
      auto part_store = [&](int s) {
        mbar_wait_lazy<100>(bars + 8 * (B_SENT + s), 0);
        const int fi = (it_ * 8 + ((jf + 1 + s) & 7)) * 8 + jf;
#pragma unroll
        for (int v = 0; v < 2; v++)
          asm volatile("cp.async.bulk.global.shared::cta.bulk_group [%0], [%1], %2;"
                       ::"l"(g_part + (size_t)fi * 1024 + v * 512), "r"(sb + SM_X + (s == 6 ? CV_E + 2 * v * E_CH : CV_S + v * S_WG + (s & 3) * 8192)), "r"(8192) : "memory");
        asm volatile("cp.async.bulk.commit_group;" ::: "memory");
      };
      if (w == 0 && lane == 0) part_store(0);
      __syncwarp();
      {
#pragma unroll 1
      for (int G = w; G < 8; G += 2) {
        const int n = 32 * G + lane;
        uint4 c0[4], c1[4];
        if (G >= 4) {
#pragma unroll
          for (int ch = 0; ch < 4; ch++) {
            const uint8_t* kc = smem + SM_KB + ch * KC_STRIDE * 2;
            const uint32_t a = *(const unsigned short*)(kc + (384 + n) * 2), bb = *(const unsigned short*)(kc + (385 + n) * 2);
            const uint32_t aa = a | (a << 16), b2 = bb | (bb << 16);
            const uint32_t tie = (n & 1) ? bb : a;
            c0[ch] = make_uint4(aa, a | (tie << 16), b2, b2);
            c1[ch] = make_uint4(aa, tie | (bb << 16), b2, b2);
          }
        } else if (G >= 2) {
#pragma unroll
          for (int ch = 0; ch < 4; ch++) {
            const uint8_t* kc = smem + SM_KB + ch * KC_STRIDE * 2;
            const uint32_t w0 = *(const uint32_t*)(kc + (256 + 2 * n) * 2), w1 = *(const uint32_t*)(kc + (258 + 2 * n) * 2);
            c0[ch] = make_uint4(dup_lo(w0), dup_hi(w0), __byte_perm(w0, w1, 0x5432), dup_lo(w1));
            c1[ch] = make_uint4(w0, dup_hi(w0), dup_lo(w1), dup_lo(w1));
          }
        } else if (G == 1) {
#pragma unroll
          for (int ch = 0; ch < 4; ch++) {
            const uint8_t* kc = smem + SM_KB + ch * KC_STRIDE * 2;
            const uint2 w01 = *(const uint2*)(kc + (128 + 4 * n) * 2);
            const uint32_t w2 = *(const uint32_t*)(kc + (132 + 4 * n) * 2);
            c0[ch] = make_uint4(w01.x, dup_lo(w01.y), w01.y, dup_lo(w2));
            c1[ch] = make_uint4(__byte_perm(w01.x, w01.y, 0x5432), dup_lo(w01.y), __byte_perm(w01.y, w2, 0x5432), dup_lo(w2));
          }
        } else {
#pragma unroll
          for (int ch = 0; ch < 4; ch++) {
            const uint8_t* kc = smem + SM_KB + ch * KC_STRIDE * 2;
            const uint4 wv = *(const uint4*)(kc + (8 * n) * 2);
            const uint32_t w4 = *(const uint32_t*)(kc + (8 * n + 8) * 2);
            c0[ch] = make_uint4(__byte_perm(wv.x, wv.y, 0x5432), __byte_perm(wv.y, wv.z, 0x5432), __byte_perm(wv.z, wv.w, 0x5432), __byte_perm(wv.w, w4, 0x5432));
            c1[ch] = make_uint4(wv.y, wv.z, wv.w, (n == 31) ? dup_lo(w4) : w4);
          }
          if (lane < 8) {
            const int ch = lane >> 1, hi = lane & 1;
            const uint32_t k01 = *(const uint32_t*)(smem + SM_KB + ch * KC_STRIDE * 2);
            uint8_t* e = smem + SM_X + CV_E + ch * E_CH + hi * 16;
            *(uint4*)e = make_uint4(0, 0, 0, hi ? (k01 << 16) : 0u);
            *(uint4*)(e + E_COPY) = make_uint4(0, 0, 0, hi ? k01 : 0u);
          }
        }
#pragma unroll
        for (int ch = 0; ch < 4; ch++) {
          uint8_t* e = smem + SM_X + CV_E + ch * E_CH + (n + 2) * 16;
          *(uint4*)e = c0[ch];
          *(uint4*)(e + E_COPY) = c1[ch];
        }
      }
        fence_async();
        __syncwarp();
        if (lane == 0) mbar_arrive(bars + 8 * B_RRDY);
        TM_IF(wt == 0, 19);
      }
      if (lane == 0) {
        const uint32_t tag = ld_epoch() + 1;
        auto publish = [&](int s) {
          asm volatile("st.relaxed.gpu.global.u32 [%0], %1;" ::"l"(g_flag + ((it_ * 8 + ((jf + 1 + s) & 7)) * 8 + jf)), "r"(tag) : "memory");
          TM_IF(true, 3 + s);
        };
#pragma unroll 1
        for (int s = w; s < 7; s += 2) {
          if (s > 0) part_store(s);
          asm volatile("cp.async.bulk.wait_group.read 0;" ::: "memory");
          mbar_arrive(bars + 8 * (B_STF + s));
          if (s >= 2 && s < 6) {
            asm volatile("cp.async.bulk.wait_group 1;" ::: "memory");
            publish(s - 2);
          }
          if (s >= 4) {
            asm volatile("cp.async.bulk.wait_group 0;" ::: "memory");
            publish(s);
          }
        }
      }
      __syncwarp();
    }
    bar_sync(2, 128);
    if (tid == 256) {
      const uint32_t tk = atomicAdd(&g_exit, 1u);
      if (tk == NCTA - 1) {
        g_exit = 0;
        *(volatile uint32_t*)&g_epoch = ld_epoch() + 1;
      }
    }
    TM_IF(tid == 256, 13);
  } else {
    asm volatile("setmaxnreg.inc.sync.aligned.u32 200;");
    const int wg = warp >> 2;
    const int g = lane >> 2, q = lane & 3;
    const uint32_t dsk = *(const uint32_t*)(P.D_skip + d0 + 2 * wg);
    uint32_t hf[56];
    {
      float acc[128];
#pragma unroll
      for (int i = 0; i < 128; i++) zero_reg(acc[i]);
#pragma unroll 1
      for (int st = 0; st < 16; st++) {
        const int slot = st % 5;
        if ((st & 1) == 0) mbar_wait(bars + 8 * (B_XFULL + (st >> 1)), 0);
        mbar_wait(bars + 8 * (B_FULL + slot), (st / 5) & 1);
        const uint64_t da = mkdesc(sb + SM_X + (st >> 1) * 16384 + wg * 8192 + (st & 1) * 64, 16, 1024, 1);
        const uint64_t db = mkdesc(sb + SM_RING + slot * 16384, 4096, 1024, 1);
        wg_fence();
        wgmma_ss_n256(acc, da, db);
        wgmma_ss_n256(acc, da + 2, db + 128);
        wg_commit();
        if (st > 0) {
          wg_wait<1>();
          if (lane == 0) mbar_arrive(bars + 8 * (B_EMPTY + (st - 1) % 5));
        }
      }
      wg_wait<0>();
      if (lane == 0) mbar_arrive(bars + 8 * (B_EMPTY + 15 % 5));
#pragma unroll
      for (int m = 0; m < 16; m++) {
        hf[2 * m] = hmul2_bf16(pack_bf16(acc[4 * m], acc[4 * m + 1]), pack_bf16(acc[64 + 4 * m], acc[64 + 4 * m + 1]));
        hf[2 * m + 1] = hmul2_bf16(pack_bf16(acc[4 * m + 2], acc[4 * m + 3]), pack_bf16(acc[64 + 4 * m + 2], acc[64 + 4 * m + 3]));
      }
    }
    {
      float accg[48], accu[48];
#pragma unroll
      for (int i = 0; i < 48; i++) { zero_reg(accg[i]); zero_reg(accu[i]); }
      const uint32_t xrow = sb + SM_X + (wg * 64 + (warp & 3) * 16 + (lane & 15)) * 128;
      const uint32_t xsw = lane & 7, xhi = lane >> 4;
      uint32_t a0[4], a1[4], a2[4], a3[4];
#pragma unroll 1
      for (int kb = 0; kb < 8; kb++) {
        const uint32_t xb = xrow + kb * 16384;
        {
          const int st = 16 + 2 * kb, slot = st % 5;
          ldsm4(a0, xb + (((0 + xhi) ^ xsw) << 4));
          ldsm4(a1, xb + (((2 + xhi) ^ xsw) << 4));
          mbar_wait(bars + 8 * (B_FULL + slot), (st / 5) & 1);
          const uint64_t db = mkdesc(sb + SM_RING + slot * 16384, 4096, 1024, 1);
          wg_fence();
          wgmma_rs_n96(accg, a0[0], a0[1], a0[2], a0[3], db);
          wgmma_rs_n96(accu, a0[0], a0[1], a0[2], a0[3], db + 512);
          wgmma_rs_n96(accg, a1[0], a1[1], a1[2], a1[3], db + 128);
          wgmma_rs_n96(accu, a1[0], a1[1], a1[2], a1[3], db + 128 + 512);
          wg_commit();
          wg_wait<1>();
          if (kb > 0 && lane == 0) mbar_arrive(bars + 8 * (B_EMPTY + (st - 1) % 5));
        }
        {
          const int st = 17 + 2 * kb, slot = st % 5;
          ldsm4(a2, xb + (((4 + xhi) ^ xsw) << 4));
          ldsm4(a3, xb + (((6 + xhi) ^ xsw) << 4));
          mbar_wait(bars + 8 * (B_FULL + slot), (st / 5) & 1);
          const uint64_t db = mkdesc(sb + SM_RING + slot * 16384, 4096, 1024, 1);
          wg_fence();
          wgmma_rs_n96(accg, a2[0], a2[1], a2[2], a2[3], db);
          wgmma_rs_n96(accu, a2[0], a2[1], a2[2], a2[3], db + 512);
          wgmma_rs_n96(accg, a3[0], a3[1], a3[2], a3[3], db + 128);
          wgmma_rs_n96(accu, a3[0], a3[1], a3[2], a3[3], db + 128 + 512);
          wg_commit();
          wg_wait<1>();
          if (lane == 0) mbar_arrive(bars + 8 * (B_EMPTY + (st - 1) % 5));
        }
      }
      wg_wait<0>();
      if (lane == 0) { mbar_arrive(bars + 8 * (B_EMPTY + 31 % 5)); mbar_arrive(bars + 8 * (B_XFREE + 7)); }
#pragma unroll
      for (int m = 0; m < 12; m++) {
        hf[32 + 2 * m] = hmul2_bf16(pack_bf16(accg[4 * m], accg[4 * m + 1]), pack_bf16(accu[4 * m], accu[4 * m + 1]));
        hf[32 + 2 * m + 1] = hmul2_bf16(pack_bf16(accg[4 * m + 2], accg[4 * m + 3]), pack_bf16(accu[4 * m + 2], accu[4 * m + 3]));
      }
    }
    float accA[32], accB[32];
    auto issue_half = [&](float (&acc)[32], int s, auto half_tag) {
      constexpr int half = decltype(half_tag)::value;
      if (half == 0) {
#pragma unroll
        for (int i = 0; i < 32; i++) zero_reg(acc[i]);
      }
      const int st = 32 + 2 * s + half;
      const int slot = st % 5;
      mbar_wait(bars + 8 * (B_FULL + slot), (st / 5) & 1);
      uint32_t sbase;
      asm volatile("mov.b32 %0, %1;" : "=r"(sbase) : "r"(sb + SM_RING + slot * 16384));
      const uint64_t db = mkdesc(sbase, 1024, 1024, 1);
      wg_fence();
#pragma unroll
      for (int k = 0; k < 7; k++) {
        const int ks = 7 * half + k;
        wgmma_rs_n64t(acc, hf[4 * ks], hf[4 * ks + 1], hf[4 * ks + 2], hf[4 * ks + 3], db + k * 128);
      }
      wg_commit();
    };
    auto release = [&](int st) { if (lane == 0) mbar_arrive(bars + 8 * (B_EMPTY + st % 5)); };
    using H0 = IC<0>;
    using H1 = IC<1>;
    auto send_pass = [&](float (&acc)[32], int s) {
      uint4* dst = (uint4*)(smem + SM_X + (s == 6 ? CV_E + 2 * wg * E_CH : CV_S + wg * S_WG + (s & 3) * 8192) + (warp & 3) * 2048) + lane;
#pragma unroll
      for (int c = 0; c < 4; c++) {
        uint4 v;
        v.x = pack_bf16(acc[8 * c], acc[8 * c + 1]); v.y = pack_bf16(acc[8 * c + 2], acc[8 * c + 3]);
        v.z = pack_bf16(acc[8 * c + 4], acc[8 * c + 5]); v.w = pack_bf16(acc[8 * c + 6], acc[8 * c + 7]);
        dst[c * 32] = v;
      }
      fence_async();
      __syncwarp();
      if (lane == 0) mbar_arrive(bars + 8 * (B_SENT + s));
    };
    auto part_load = [&](uint4 (&v)[4], int k) {
      mbar_wait(bars + 8 * (B_GOT + k), 0);
      const uint4* sp = g_part + (size_t)(((it_ * 8 + jf) * 8 + ((jf - k) & 7)) * 8 + warp) * 128 + lane;
#pragma unroll
      for (int c = 0; c < 4; c++) v[c] = ld_cg4(sp + c * 32);
    };
    auto part_add = [&](const uint4 (&v)[4]) {
#pragma unroll
      for (int c = 0; c < 4; c++) {
        accA[8 * c] += bf_lo(v[c].x); accA[8 * c + 1] += bf_hi(v[c].x); accA[8 * c + 2] += bf_lo(v[c].y); accA[8 * c + 3] += bf_hi(v[c].y);
        accA[8 * c + 4] += bf_lo(v[c].z); accA[8 * c + 5] += bf_hi(v[c].z); accA[8 * c + 6] += bf_lo(v[c].w); accA[8 * c + 7] += bf_hi(v[c].w);
      }
    };
    mbar_wait(bars + 8 * (B_XFREE + 7), 0);
    issue_half(accA, 0, H0{});
    issue_half(accA, 0, H1{}); wg_wait<1>(); release(32);
    issue_half(accB, 1, H0{}); wg_wait<1>(); release(33); send_pass(accA, 0);
    issue_half(accB, 1, H1{}); wg_wait<1>(); release(34);
    issue_half(accA, 2, H0{}); wg_wait<1>(); release(35); send_pass(accB, 1);
    issue_half(accA, 2, H1{}); wg_wait<1>(); release(36);
    issue_half(accB, 3, H0{}); wg_wait<1>(); release(37); send_pass(accA, 2);
    issue_half(accB, 3, H1{}); wg_wait<1>(); release(38);
    issue_half(accA, 4, H0{}); wg_wait<1>(); release(39); send_pass(accB, 3);
    issue_half(accA, 4, H1{}); wg_wait<1>(); release(40);
    issue_half(accB, 5, H0{}); wg_wait<1>(); release(41); mbar_wait(bars + 8 * (B_STF + 0), 0); send_pass(accA, 4);
    issue_half(accB, 5, H1{}); wg_wait<1>(); release(42);
    wg_wait<0>(); mbar_wait(bars + 8 * (B_STF + 1), 0); send_pass(accB, 5);
    {
      TM_IF(tid == 0, 10);
      const int w = warp & 3;
      mbar_wait(bars + 8 * B_RRDY, 0);
      TM_IF(tid == 0, 11);
      const uint32_t zero = lds32(sb + SM_X + CV_R + 128 * 16);
      const int c = tid & 127;
      const float* Sr = (const float*)(smem + SM_X + CV_S + wg * S_WG) + (127 - c);
      float* Sw = (float*)(smem + SM_X + CV_S + wg * S_WG) + w * 16 * S_PITCH + g * S_PITCH + 2 * q;
      float acc[4][16];
      uint32_t fa[4][4], fb[4][4];
      uint32_t ares[8], rv[8];
      auto stage_out = [&]() {
#pragma unroll
        for (int m = 0; m < 16; m++) {
          *(float2*)(Sw + 8 * m) = make_float2(acc[m >> 2][4 * (m & 3)], acc[m >> 2][4 * (m & 3) + 1]);
          *(float2*)(Sw + 8 * S_PITCH + 8 * m) = make_float2(acc[m >> 2][4 * (m & 3) + 2], acc[m >> 2][4 * (m & 3) + 3]);
        }
      };
      auto load_u = [&](int ch) {
        const uint4 r0v = *(const uint4*)(smem + SM_X + CV_R + ch * R_CH + (127 - c) * 16);
        const uint4 r1v = *(const uint4*)(smem + SM_X + CV_R + ch * R_CH + R_HALF + (127 - c) * 16);
        rv[0] = r0v.x; rv[1] = r0v.y; rv[2] = r0v.z; rv[3] = r0v.w; rv[4] = r1v.x; rv[5] = r1v.y; rv[6] = r1v.z; rv[7] = r1v.w;
      };
#define POST(r2, dk2)                                                                              \
      {                                                                                            \
        float y_[2];                                                                               \
        _Pragma("unroll") for (int t2 = 0; t2 < 2; t2++) {                                         \
          const int r0 = 2 * (r2) + t2;                                                            \
          const float s1 = c >= 1 ? Sr[(16 + r0) * S_PITCH + 1] : 0.f;                             \
          const float s2 = c >= 2 ? Sr[(32 + r0) * S_PITCH + 2] : 0.f;                             \
          const float s3 = c >= 3 ? Sr[(48 + r0) * S_PITCH + 3] : 0.f;                             \
          y_[t2] = (Sr[r0 * S_PITCH] + s1) + (s2 + s3);                                            \
        }                                                                                          \
        ares[r2] = hadd2_bf16(pack_bf16(y_[0], y_[1]), hmul2_bf16(__byte_perm(rv[7 - (r2)], rv[7 - (r2)], 0x1032), dk2)); \
      }
      auto store_a = [&](int ch) {
        uint4* ap = (uint4*)(smem + SM_X + CV_R + ch * R_CH + c * 32);
        ap[0] = make_uint4(ares[0], ares[1], ares[2], ares[3]);
        ap[1] = make_uint4(ares[4], ares[5], ares[6], ares[7]);
        fence_async();
      };
      const uint32_t eoff = ((g & 1) ? E_COPY : 0) + (16 * w + (g & ~1) + 2 * q) * 2;
      const uint32_t dkA = dup_lo(dsk), dkB = dup_hi(dsk);
      {
        const int ch = 2 * wg;
        const uint32_t ebase = sb + SM_X + CV_E + ch * E_CH + eoff;
        const uint64_t de = mkdesc(sb + SM_X + CV_R + ch * R_CH, R_HALF, 128, 0);
        conv_load4<0>(fa, ebase, zero);
        conv_load4<4>(fb, ebase, zero);
        conv_issue4<0>(acc, fa, de);
        conv_issue4<4>(acc, fb, de);
        wg_wait<1>(); conv_load4<8>(fa, ebase, zero);  conv_issue4<8>(acc, fa, de);
        wg_wait<1>(); conv_load4<12>(fb, ebase, zero); conv_issue4<12>(acc, fb, de);
        wg_wait<1>(); conv_load4<16>(fa, ebase, zero); conv_issue4<16>(acc, fa, de);
        wg_wait<1>(); conv_load4<20>(fb, ebase, zero); conv_issue4<20>(acc, fb, de);
        wg_wait<1>(); conv_load4<24>(fa, ebase, zero); conv_issue4<24>(acc, fa, de);
        wg_wait<1>(); conv_load4<28>(fb, ebase, zero); conv_issue4<28>(acc, fb, de);
#pragma unroll 1
        for (int s = 2; s < 6; s++) mbar_wait(bars + 8 * (B_STF + s), 0);
        load_u(ch);
        wg_wait<0>();
        TM_IF(tid == 0, 12);
        stage_out();
        TM_IF(tid == 0, 14);
      }
      issue_half(accA, 6, H0{});
      issue_half(accA, 6, H1{});
      bar_sync(6 + wg, 128);
      POST(0, dkA) POST(1, dkA) POST(2, dkA) POST(3, dkA) POST(4, dkA) POST(5, dkA) POST(6, dkA) POST(7, dkA)
      store_a(2 * wg);
      __syncwarp();
      if (lane == 0) mbar_arrive(bars + 8 * B_ADONE);
      {
        const int ch = 2 * wg + 1;
        const uint32_t ebase = sb + SM_X + CV_E + ch * E_CH + eoff;
        const uint64_t de = mkdesc(sb + SM_X + CV_R + ch * R_CH, R_HALF, 128, 0);
        conv_load4<0>(fa, ebase, zero);
        conv_load4<4>(fb, ebase, zero);
        wg_wait<0>();
        send_pass(accA, 6);
        conv_issue4<0>(acc, fa, de);
        conv_issue4<4>(acc, fb, de);
        wg_wait<1>(); conv_load4<8>(fa, ebase, zero);  conv_issue4<8>(acc, fa, de);
        wg_wait<1>(); conv_load4<12>(fb, ebase, zero); conv_issue4<12>(acc, fb, de);
        wg_wait<1>(); conv_load4<16>(fa, ebase, zero); conv_issue4<16>(acc, fa, de);
        wg_wait<1>(); conv_load4<20>(fb, ebase, zero); conv_issue4<20>(acc, fb, de);
        wg_wait<1>(); conv_load4<24>(fa, ebase, zero); conv_issue4<24>(acc, fa, de);
        wg_wait<1>(); conv_load4<28>(fb, ebase, zero); conv_issue4<28>(acc, fb, de);
        bar_sync(6 + wg, 128);
        load_u(ch);
        wg_wait<0>();
        TM_IF(tid == 0, 15);
        stage_out();
        bar_sync(6 + wg, 128);
        TM_IF(tid == 0, 17);
        POST(0, dkB) POST(1, dkB) POST(2, dkB) POST(3, dkB) POST(4, dkB) POST(5, dkB) POST(6, dkB) POST(7, dkB)
        store_a(ch);
        __syncwarp();
        if (lane == 0) mbar_arrive(bars + 8 * B_ADONE);
      }
      issue_half(accB, 7, H0{});
      issue_half(accB, 7, H1{});
#undef POST
    }
    {
#pragma unroll
      for (int i = 0; i < 32; i++) accA[i] = 0.f;
      uint4 v0[4], v1[4], v2[4];
      part_load(v0, 1);
      part_load(v1, 2);
      part_load(v2, 3);
      part_add(v0); part_load(v0, 4);
      part_add(v1); part_load(v1, 5);
      part_add(v2); part_load(v2, 6);
      part_add(v0); part_load(v0, 7);
      part_add(v1);
      part_add(v2);
      part_add(v0);
    }
    mbar_wait(bars + 8 * B_ATILE, 0);
    const int row0 = it_ * 128 + warp * 16 + g;
    const float g0 = __ldcg(g_gate + row0), g1 = __ldcg(g_gate + row0 + 8);
    uint32_t av[16];
    {
      const int dl = (lane & 7) + ((lane >> 4) << 3);
      const int chunk = 2 * (warp & 3) + ((lane >> 3) & 1);
      const uint32_t abase = sb + SM_AT + wg * 8192 + dl * 128 + ((chunk ^ (lane & 7)) << 4);
#pragma unroll
      for (int m2 = 0; m2 < 4; m2++) {
        asm volatile("ldmatrix.sync.aligned.m8n8.x4.trans.shared.b16 {%0,%1,%2,%3}, [%4];"
                     : "=r"(av[4 * m2]), "=r"(av[4 * m2 + 1]), "=r"(av[4 * m2 + 2]), "=r"(av[4 * m2 + 3]) : "r"(abase + m2 * 2048) : "memory");
      }
    }
    wg_wait<0>();
    const uint32_t gg0 = pack_bf16(g0, g0), gg1 = pack_bf16(g1, g1);
    const uint32_t og0 = pack_bf16(1.f - g0, 1.f - g0), og1 = pack_bf16(1.f - g1, 1.f - g1);
#pragma unroll
    for (int m = 0; m < 8; m++) {
      const uint32_t b0 = pack_bf16(accA[4 * m] + accB[4 * m], accA[4 * m + 1] + accB[4 * m + 1]);
      const uint32_t b1 = pack_bf16(accA[4 * m + 2] + accB[4 * m + 2], accA[4 * m + 3] + accB[4 * m + 3]);
      const uint32_t o0 = hadd2_bf16(hmul2_bf16(gg0, av[2 * m]), hmul2_bf16(og0, b0));
      const uint32_t o1 = hadd2_bf16(hmul2_bf16(gg1, av[2 * m + 1]), hmul2_bf16(og1, b1));
      *(uint32_t*)(P.out + row0 * D_ + jf * 64 + 8 * m + 2 * q) = o0;
      *(uint32_t*)(P.out + (row0 + 8) * D_ + jf * 64 + 8 * m + 2 * q) = o1;
    }
  }
}

typedef CUresult (*EncFn)(CUtensorMap*, CUtensorMapDataType, cuuint32_t, void*, const cuuint64_t*, const cuuint64_t*, const cuuint32_t*,
                          const cuuint32_t*, CUtensorMapInterleave, CUtensorMapSwizzle, CUtensorMapL2promotion, CUtensorMapFloatOOBfill);

struct HostState {
  bool ready;
  const void* key[4];
  Maps M;
};
HostState hs;

}

extern "C" void kernel_launch(void* const* d_in, const int* in_sizes, int n_in, void* d_out, int out_size) {
  (void)in_sizes; (void)n_in; (void)out_size;
  void* x = d_in[0];
  void* wg = d_in[8];
  void* wu = d_in[9];
  void* wd = d_in[10];
  if (!hs.ready || hs.key[0] != x || hs.key[1] != wg || hs.key[2] != wu || hs.key[3] != wd) {
    void* fn = nullptr;
    cudaDriverEntryPointQueryResult qr;
    cudaGetDriverEntryPoint("cuTensorMapEncodeTiled", &fn, cudaEnableDefault, &qr);
    EncFn enc = (EncFn)fn;
    const cuuint32_t es[3] = {1, 1, 1};
    const CUtensorMapDataType BF = CU_TENSOR_MAP_DATA_TYPE_BFLOAT16;
    const CUtensorMapInterleave IN = CU_TENSOR_MAP_INTERLEAVE_NONE;
    const CUtensorMapL2promotion PR = CU_TENSOR_MAP_L2_PROMOTION_L2_128B;
    const CUtensorMapFloatOOBfill OO = CU_TENSOR_MAP_FLOAT_OOB_FILL_NONE;
    {
      cuuint64_t gd[2] = {(cuuint64_t)D_, (cuuint64_t)L_}; cuuint64_t gs[1] = {(cuuint64_t)D_ * 2}; cuuint32_t box[2] = {64, 128};
      enc(&hs.M.X, BF, 2, x, gd, gs, box, es, IN, CU_TENSOR_MAP_SWIZZLE_128B, PR, OO);
    }
    {
      cuuint64_t gd[2] = {(cuuint64_t)F_, (cuuint64_t)D_}; cuuint64_t gs[1] = {(cuuint64_t)F_ * 2}; cuuint32_t box[2] = {64, 32};
      enc(&hs.M.Wg, BF, 2, wg, gd, gs, box, es, IN, CU_TENSOR_MAP_SWIZZLE_128B, PR, OO);
      enc(&hs.M.Wu, BF, 2, wu, gd, gs, box, es, IN, CU_TENSOR_MAP_SWIZZLE_128B, PR, OO);
      for (int o = 0; o < 2; o++) {
        cuuint64_t gd3[3] = {64, (cuuint64_t)D_, (cuuint64_t)(F_ / 64 - o)}; cuuint64_t gs3[2] = {(cuuint64_t)F_ * 2, 128};
        cuuint32_t box3[3] = {64, 32, 2};
        enc(&hs.M.Wg3[o], BF, 3, (char*)wg + 64 * o, gd3, gs3, box3, es, IN, CU_TENSOR_MAP_SWIZZLE_128B, PR, OO);
        enc(&hs.M.Wu3[o], BF, 3, (char*)wu + 64 * o, gd3, gs3, box3, es, IN, CU_TENSOR_MAP_SWIZZLE_128B, PR, OO);
      }
    }
    {
      cuuint64_t gd[2] = {(cuuint64_t)D_, (cuuint64_t)F_}; cuuint64_t gs[1] = {(cuuint64_t)D_ * 2}; cuuint32_t box[2] = {64, 112};
      enc(&hs.M.Wd, BF, 2, wd, gd, gs, box, es, IN, CU_TENSOR_MAP_SWIZZLE_128B, PR, OO);
    }
    {
      void* pa = nullptr;
      cudaGetSymbolAddress(&pa, g_aT);
      cuuint64_t gd[2] = {(cuuint64_t)L_, (cuuint64_t)D_}; cuuint64_t gs[1] = {(cuuint64_t)L_ * 2}; cuuint32_t box[2] = {64, 64};
      enc(&hs.M.AT, BF, 2, pa, gd, gs, box, es, IN, CU_TENSOR_MAP_SWIZZLE_128B, PR, OO);
    }
    cudaFuncSetAttribute(fused_kernel, cudaFuncAttributeMaxDynamicSharedMemorySize, SM_TOTAL);
    hs.key[0] = x; hs.key[1] = wg; hs.key[2] = wu; hs.key[3] = wd;
    hs.ready = true;
  }
  Params P;
  P.x = (const __nv_bfloat16*)d_in[0];
  P.log_A_real = (const __nv_bfloat16*)d_in[1];
  P.A_imag = (const __nv_bfloat16*)d_in[2];
  P.C_real = (const __nv_bfloat16*)d_in[3];
  P.C_imag = (const __nv_bfloat16*)d_in[4];
  P.log_dt = (const __nv_bfloat16*)d_in[5];
  P.D_skip = (const __nv_bfloat16*)d_in[6];
  P.gate_w = (const __nv_bfloat16*)d_in[11];
  P.w_gate = (const __nv_bfloat16*)wg;
  P.w_up = (const __nv_bfloat16*)wu;
  P.w_down = (const __nv_bfloat16*)wd;
  P.out = (__nv_bfloat16*)d_out;
  fused_kernel<<<NCTA, NTHREADS, SM_TOTAL>>>(hs.M, P);
}
```

```cpp
#include <cuda_runtime.h>
#include <cuda_bf16.h>
#include <cuda.h>
#include <stdint.h>

#define PUBMODE 2
namespace {

constexpr int L_ = 2048, D_ = 512, F_ = 1792, NS_ = 128;
constexpr int NCTA = 128;
constexpr int NTHREADS = 384;

constexpr int SM_X = 0;
constexpr int SM_RING = 131072;
constexpr int KC_STRIDE = 656;
constexpr int SM_KB = 212992;
constexpr int SM_PR = SM_KB + 4 * KC_STRIDE * 2;
constexpr int PR_WARP = 64 * 24;
constexpr int SM_BAR = SM_PR + 512 * 24;
constexpr int SM_TOTAL = SM_BAR + 512;
constexpr int CV_R = 0;
constexpr int R_HALF = 156 * 16;
constexpr int R_CH = 2 * R_HALF;
constexpr int CV_E = 4 * R_CH;
constexpr int E_COPY = 4160;
constexpr int E_CH = 2 * E_COPY;
constexpr int CV_S = CV_E + 4 * E_CH;
constexpr int S_PITCH = 136;
constexpr int S_WG = 4 * 16 * S_PITCH * 4;
constexpr int SM_AT = SM_X;
static_assert(CV_S + 2 * S_WG <= 131072, "conv region");

constexpr int B_FULL = 0, B_EMPTY = 5, B_XFULL = 10, B_XFREE = 18, B_ATILE = 26, B_RRDY = 27, B_ADONE = 28, B_KPART = 29, B_KSUM = 30, B_SENT = 35, B_GOT = 43, B_STF = 51;

__device__ uint4 g_part[16 * 8 * 8 * 8 * 4 * 32];
__device__ uint32_t g_flag[16 * 8 * 8];
__device__ __align__(1024) __nv_bfloat16 g_aT[D_ * L_];
__device__ float g_gate[L_];
__device__ uint32_t g_done1;
__device__ uint32_t g_cnt[8 * 32];
__device__ uint32_t g_exit;
__device__ uint32_t g_zero;
__device__ uint32_t g_epoch;

#define TM_IF(cond, idx) do {} while (0)
#define FAIL(a, ph) break
#define SPIN_LIMIT (1 << 22)
#define MBAR_LIMIT (1 << 20)
__device__ __forceinline__ uint32_t smem_u32(const void* p) { return (uint32_t)__cvta_generic_to_shared(p); }
__device__ __forceinline__ void mbar_init(uint32_t a, uint32_t c) { asm volatile("mbarrier.init.shared::cta.b64 [%0], %1;" ::"r"(a), "r"(c) : "memory"); }
__device__ __forceinline__ void mbar_expect(uint32_t a, uint32_t bytes) { asm volatile("mbarrier.arrive.expect_tx.shared::cta.b64 _, [%0], %1;" ::"r"(a), "r"(bytes) : "memory"); }
__device__ __forceinline__ void mbar_arrive(uint32_t a) { asm volatile("mbarrier.arrive.shared::cta.b64 _, [%0];" ::"r"(a) : "memory"); }
__device__ __forceinline__ void mbar_wait(uint32_t a, uint32_t ph) {
  asm volatile("{\n.reg .pred p;\n.reg .u32 c;\nmov.u32 c, 0;\nLW:\nmbarrier.try_wait.parity.shared::cta.b64 p, [%0], %1, %2;\n@p bra LD;\n"
               "add.u32 c, c, 1;\nsetp.lt.u32 p, c, 1048576;\n@p bra LW;\nLD:\n}" ::"r"(a), "r"(ph), "r"(20000u) : "memory");
}
template <int NS> __device__ __forceinline__ void mbar_wait_lazy(uint32_t a, uint32_t ph) {
  asm volatile("{\n.reg .pred p;\n.reg .u32 c;\nmov.u32 c, 0;\nLW:\nmbarrier.test_wait.parity.shared::cta.b64 p, [%0], %1;\n@p bra LD;\n"
               "nanosleep.u32 %2;\nadd.u32 c, c, 1;\nsetp.lt.u32 p, c, 4194304;\n@p bra LW;\nLD:\n}" ::"r"(a), "r"(ph), "n"(NS) : "memory");
}
__device__ __forceinline__ void tma2d(uint32_t dst, const CUtensorMap* m, int c0, int c1, uint32_t bar) {
  asm volatile("cp.async.bulk.tensor.2d.shared::cluster.global.mbarrier::complete_tx::bytes [%0], [%1, {%3,%4}], [%2];" ::"r"(dst), "l"(m), "r"(bar), "r"(c0), "r"(c1) : "memory");
}
__device__ __forceinline__ void tma3d(uint32_t dst, const CUtensorMap* m, int c0, int c1, int c2, uint32_t bar) {
  asm volatile("cp.async.bulk.tensor.3d.shared::cluster.global.mbarrier::complete_tx::bytes [%0], [%1, {%3,%4,%5}], [%2];" ::"r"(dst), "l"(m), "r"(bar), "r"(c0), "r"(c1), "r"(c2) : "memory");
}
__device__ __forceinline__ uint64_t mkdesc(uint32_t addr, uint32_t lbo, uint32_t sbo, uint32_t sw) {
  return (uint64_t)((addr & 0x3FFFF) >> 4) | ((uint64_t)(lbo >> 4) << 16) | ((uint64_t)(sbo >> 4) << 32) | ((uint64_t)sw << 62);
}
__device__ __forceinline__ void wg_fence() { asm volatile("wgmma.fence.sync.aligned;" ::: "memory"); }
__device__ __forceinline__ void wg_commit() { asm volatile("wgmma.commit_group.sync.aligned;" ::: "memory"); }
template <int N> __device__ __forceinline__ void wg_wait() { asm volatile("wgmma.wait_group.sync.aligned %0;" ::"n"(N) : "memory"); }
__device__ __forceinline__ void zero_reg(float& x) { asm volatile("mov.f32 %0, 0f00000000;" : "=f"(x)); }
__device__ __forceinline__ void movf(float& d, float s) { asm volatile("mov.f32 %0, %1;" : "=f"(d) : "f"(s)); }
__device__ __forceinline__ void bar_sync(int id, int n) { asm volatile("bar.sync %0, %1;" ::"r"(id), "r"(n) : "memory"); }
__device__ __forceinline__ void fence_async() { asm volatile("fence.proxy.async.shared::cta;" ::: "memory"); }
__device__ __forceinline__ uint32_t pack_bf16(float lo, float hi) {
  uint32_t r;
  asm("cvt.rn.bf16x2.f32 %0, %1, %2;" : "=r"(r) : "f"(hi), "f"(lo));
  return r;
}
__device__ __forceinline__ uint32_t hmul2_bf16(uint32_t a, uint32_t b) {
  uint32_t r;
  asm("mul.rn.bf16x2 %0, %1, %2;" : "=r"(r) : "r"(a), "r"(b));
  return r;
}
__device__ __forceinline__ uint32_t hadd2_bf16(uint32_t a, uint32_t b) {
  uint32_t r;
  asm("add.rn.bf16x2 %0, %1, %2;" : "=r"(r) : "r"(a), "r"(b));
  return r;
}
__device__ __forceinline__ float bf_lo(uint32_t v) { return __uint_as_float(v << 16); }
__device__ __forceinline__ float bf_hi(uint32_t v) { return __uint_as_float(v & 0xFFFF0000u); }
__device__ __forceinline__ float bf16r(float x) { return __bfloat162float(__float2bfloat16_rn(x)); }
__device__ __forceinline__ float ldbf(const __nv_bfloat16* p) { return __bfloat162float(*p); }
__device__ __forceinline__ uint32_t ld_acquire(const uint32_t* p) {
  uint32_t v;
  asm volatile("ld.acquire.gpu.global.u32 %0, [%1];" : "=r"(v) : "l"(p) : "memory");
  return v;
}
__device__ __forceinline__ void st_release(uint32_t* p, uint32_t v) { asm volatile("st.release.gpu.global.u32 [%0], %1;" ::"l"(p), "r"(v) : "memory"); }
__device__ __forceinline__ uint4 ld_cg4(const uint4* p) {
  uint4 v;
  asm volatile("ld.global.cg.v4.u32 {%0,%1,%2,%3}, [%4];" : "=r"(v.x), "=r"(v.y), "=r"(v.z), "=r"(v.w) : "l"(p) : "memory");
  return v;
}
__device__ __forceinline__ uint32_t ld_cg1(const void* p) {
  uint32_t v;
  asm volatile("ld.global.cg.u32 %0, [%1];" : "=r"(v) : "l"(p) : "memory");
  return v;
}
__device__ __forceinline__ uint32_t lds32(uint32_t a) {
  uint32_t v;
  asm volatile("ld.shared.u32 %0, [%1];" : "=r"(v) : "r"(a) : "memory");
  return v;
}
__device__ __forceinline__ void ldsm4(uint32_t (&r)[4], uint32_t a) {
  asm volatile("ldmatrix.sync.aligned.m8n8.x4.shared.b16 {%0,%1,%2,%3}, [%4];" : "=r"(r[0]), "=r"(r[1]), "=r"(r[2]), "=r"(r[3]) : "r"(a) : "memory");
}
__device__ __forceinline__ uint32_t pack_f16(float lo, float hi) {
  uint32_t r;
  asm("cvt.rn.f16x2.f32 %0, %1, %2;" : "=r"(r) : "f"(hi), "f"(lo));
  return r;
}

__device__ __forceinline__ void wgmma_ss_n256(float (&d)[128], uint64_t da, uint64_t db) {
  asm volatile("wgmma.mma_async.sync.aligned.m64n256k16.f32.bf16.bf16 {%0, %1, %2, %3, %4, %5, %6, %7, %8, %9, %10, %11, %12, %13, %14, %15, %16, %17, %18, %19, %20, %21, %22, %23, %24, %25, %26, %27, %28, %29, %30, %31, %32, %33, %34, %35, %36, %37, %38, %39, %40, %41, %42, %43, %44, %45, %46, %47, %48, %49, %50, %51, %52, %53, %54, %55, %56, %57, %58, %59, %60, %61, %62, %63, %64, %65, %66, %67, %68, %69, %70, %71, %72, %73, %74, %75, %76, %77, %78, %79, %80, %81, %82, %83, %84, %85, %86, %87, %88, %89, %90, %91, %92, %93, %94, %95, %96, %97, %98, %99, %100, %101, %102, %103, %104, %105, %106, %107, %108, %109, %110, %111, %112, %113, %114, %115, %116, %117, %118, %119, %120, %121, %122, %123, %124, %125, %126, %127}, %128, %129, 1, 1, 1, 0, 1;"
    : "+f"(d[0]), "+f"(d[1]), "+f"(d[2]), "+f"(d[3]), "+f"(d[4]), "+f"(d[5]), "+f"(d[6]), "+f"(d[7]), "+f"(d[8]), "+f"(d[9]), "+f"(d[10]), "+f"(d[11]), "+f"(d[12]), "+f"(d[13]), "+f"(d[14]), "+f"(d[15]), "+f"(d[16]), "+f"(d[17]), "+f"(d[18]), "+f"(d[19]), "+f"(d[20]), "+f"(d[21]), "+f"(d[22]), "+f"(d[23]), "+f"(d[24]), "+f"(d[25]), "+f"(d[26]), "+f"(d[27]), "+f"(d[28]), "+f"(d[29]), "+f"(d[30]), "+f"(d[31]), "+f"(d[32]), "+f"(d[33]), "+f"(d[34]), "+f"(d[35]), "+f"(d[36]), "+f"(d[37]), "+f"(d[38]), "+f"(d[39]), "+f"(d[40]), "+f"(d[41]), "+f"(d[42]), "+f"(d[43]), "+f"(d[44]), "+f"(d[45]), "+f"(d[46]), "+f"(d[47]), "+f"(d[48]), "+f"(d[49]), "+f"(d[50]), "+f"(d[51]), "+f"(d[52]), "+f"(d[53]), "+f"(d[54]), "+f"(d[55]), "+f"(d[56]), "+f"(d[57]), "+f"(d[58]), "+f"(d[59]), "+f"(d[60]), "+f"(d[61]), "+f"(d[62]), "+f"(d[63]), "+f"(d[64]), "+f"(d[65]), "+f"(d[66]), "+f"(d[67]), "+f"(d[68]), "+f"(d[69]), "+f"(d[70]), "+f"(d[71]), "+f"(d[72]), "+f"(d[73]), "+f"(d[74]), "+f"(d[75]), "+f"(d[76]), "+f"(d[77]), "+f"(d[78]), "+f"(d[79]), "+f"(d[80]), "+f"(d[81]), "+f"(d[82]), "+f"(d[83]), "+f"(d[84]), "+f"(d[85]), "+f"(d[86]), "+f"(d[87]), "+f"(d[88]), "+f"(d[89]), "+f"(d[90]), "+f"(d[91]), "+f"(d[92]), "+f"(d[93]), "+f"(d[94]), "+f"(d[95]), "+f"(d[96]), "+f"(d[97]), "+f"(d[98]), "+f"(d[99]), "+f"(d[100]), "+f"(d[101]), "+f"(d[102]), "+f"(d[103]), "+f"(d[104]), "+f"(d[105]), "+f"(d[106]), "+f"(d[107]), "+f"(d[108]), "+f"(d[109]), "+f"(d[110]), "+f"(d[111]), "+f"(d[112]), "+f"(d[113]), "+f"(d[114]), "+f"(d[115]), "+f"(d[116]), "+f"(d[117]), "+f"(d[118]), "+f"(d[119]), "+f"(d[120]), "+f"(d[121]), "+f"(d[122]), "+f"(d[123]), "+f"(d[124]), "+f"(d[125]), "+f"(d[126]), "+f"(d[127]) : "l"(da), "l"(db));
}
__device__ __forceinline__ void wgmma_rs_n96(float (&d)[48], uint32_t a0, uint32_t a1, uint32_t a2, uint32_t a3, uint64_t db) {
  asm volatile("wgmma.mma_async.sync.aligned.m64n96k16.f32.bf16.bf16 {%0, %1, %2, %3, %4, %5, %6, %7, %8, %9, %10, %11, %12, %13, %14, %15, %16, %17, %18, %19, %20, %21, %22, %23, %24, %25, %26, %27, %28, %29, %30, %31, %32, %33, %34, %35, %36, %37, %38, %39, %40, %41, %42, %43, %44, %45, %46, %47}, {%48,%49,%50,%51}, %52, 1, 1, 1, 1;"
    : "+f"(d[0]), "+f"(d[1]), "+f"(d[2]), "+f"(d[3]), "+f"(d[4]), "+f"(d[5]), "+f"(d[6]), "+f"(d[7]), "+f"(d[8]), "+f"(d[9]), "+f"(d[10]), "+f"(d[11]), "+f"(d[12]), "+f"(d[13]), "+f"(d[14]), "+f"(d[15]), "+f"(d[16]), "+f"(d[17]), "+f"(d[18]), "+f"(d[19]), "+f"(d[20]), "+f"(d[21]), "+f"(d[22]), "+f"(d[23]), "+f"(d[24]), "+f"(d[25]), "+f"(d[26]), "+f"(d[27]), "+f"(d[28]), "+f"(d[29]), "+f"(d[30]), "+f"(d[31]), "+f"(d[32]), "+f"(d[33]), "+f"(d[34]), "+f"(d[35]), "+f"(d[36]), "+f"(d[37]), "+f"(d[38]), "+f"(d[39]), "+f"(d[40]), "+f"(d[41]), "+f"(d[42]), "+f"(d[43]), "+f"(d[44]), "+f"(d[45]), "+f"(d[46]), "+f"(d[47]) : "r"(a0), "r"(a1), "r"(a2), "r"(a3), "l"(db));
}
__device__ __forceinline__ void wgmma_rs_n64t(float (&d)[32], uint32_t a0, uint32_t a1, uint32_t a2, uint32_t a3, uint64_t db) {
  asm volatile("wgmma.mma_async.sync.aligned.m64n64k16.f32.bf16.bf16 {%0, %1, %2, %3, %4, %5, %6, %7, %8, %9, %10, %11, %12, %13, %14, %15, %16, %17, %18, %19, %20, %21, %22, %23, %24, %25, %26, %27, %28, %29, %30, %31}, {%32,%33,%34,%35}, %36, 1, 1, 1, 1;"
    : "+f"(d[0]), "+f"(d[1]), "+f"(d[2]), "+f"(d[3]), "+f"(d[4]), "+f"(d[5]), "+f"(d[6]), "+f"(d[7]), "+f"(d[8]), "+f"(d[9]), "+f"(d[10]), "+f"(d[11]), "+f"(d[12]), "+f"(d[13]), "+f"(d[14]), "+f"(d[15]), "+f"(d[16]), "+f"(d[17]), "+f"(d[18]), "+f"(d[19]), "+f"(d[20]), "+f"(d[21]), "+f"(d[22]), "+f"(d[23]), "+f"(d[24]), "+f"(d[25]), "+f"(d[26]), "+f"(d[27]), "+f"(d[28]), "+f"(d[29]), "+f"(d[30]), "+f"(d[31]) : "r"(a0), "r"(a1), "r"(a2), "r"(a3), "l"(db));
}
__device__ __forceinline__ void cw128z(float (&d)[64], uint32_t a0, uint32_t a1, uint32_t a2, uint32_t a3, uint64_t db) {
  asm volatile("{.reg .pred p; setp.ne.b32 p, 0, 0; wgmma.mma_async.sync.aligned.m64n128k16.f32.bf16.bf16 {%0, %1, %2, %3, %4, %5, %6, %7, %8, %9, %10, %11, %12, %13, %14, %15, %16, %17, %18, %19, %20, %21, %22, %23, %24, %25, %26, %27, %28, %29, %30, %31, %32, %33, %34, %35, %36, %37, %38, %39, %40, %41, %42, %43, %44, %45, %46, %47, %48, %49, %50, %51, %52, %53, %54, %55, %56, %57, %58, %59, %60, %61, %62, %63}, {%64,%65,%66,%67}, %68, p, 1, 1, 0;}"
    : "=f"(d[0]), "=f"(d[1]), "=f"(d[2]), "=f"(d[3]), "=f"(d[4]), "=f"(d[5]), "=f"(d[6]), "=f"(d[7]), "=f"(d[8]), "=f"(d[9]), "=f"(d[10]), "=f"(d[11]), "=f"(d[12]), "=f"(d[13]), "=f"(d[14]), "=f"(d[15]), "=f"(d[16]), "=f"(d[17]), "=f"(d[18]), "=f"(d[19]), "=f"(d[20]), "=f"(d[21]), "=f"(d[22]), "=f"(d[23]), "=f"(d[24]), "=f"(d[25]), "=f"(d[26]), "=f"(d[27]), "=f"(d[28]), "=f"(d[29]), "=f"(d[30]), "=f"(d[31]), "=f"(d[32]), "=f"(d[33]), "=f"(d[34]), "=f"(d[35]), "=f"(d[36]), "=f"(d[37]), "=f"(d[38]), "=f"(d[39]), "=f"(d[40]), "=f"(d[41]), "=f"(d[42]), "=f"(d[43]), "=f"(d[44]), "=f"(d[45]), "=f"(d[46]), "=f"(d[47]), "=f"(d[48]), "=f"(d[49]), "=f"(d[50]), "=f"(d[51]), "=f"(d[52]), "=f"(d[53]), "=f"(d[54]), "=f"(d[55]), "=f"(d[56]), "=f"(d[57]), "=f"(d[58]), "=f"(d[59]), "=f"(d[60]), "=f"(d[61]), "=f"(d[62]), "=f"(d[63]) : "r"(a0), "r"(a1), "r"(a2), "r"(a3), "l"(db));
}
__device__ __forceinline__ void cw128(float (&d)[64], uint32_t a0, uint32_t a1, uint32_t a2, uint32_t a3, uint64_t db) {
  asm volatile("wgmma.mma_async.sync.aligned.m64n128k16.f32.bf16.bf16 {%0, %1, %2, %3, %4, %5, %6, %7, %8, %9, %10, %11, %12, %13, %14, %15, %16, %17, %18, %19, %20, %21, %22, %23, %24, %25, %26, %27, %28, %29, %30, %31, %32, %33, %34, %35, %36, %37, %38, %39, %40, %41, %42, %43, %44, %45, %46, %47, %48, %49, %50, %51, %52, %53, %54, %55, %56, %57, %58, %59, %60, %61, %62, %63}, {%64,%65,%66,%67}, %68, 1, 1, 1, 0;"
    : "+f"(d[0]), "+f"(d[1]), "+f"(d[2]), "+f"(d[3]), "+f"(d[4]), "+f"(d[5]), "+f"(d[6]), "+f"(d[7]), "+f"(d[8]), "+f"(d[9]), "+f"(d[10]), "+f"(d[11]), "+f"(d[12]), "+f"(d[13]), "+f"(d[14]), "+f"(d[15]), "+f"(d[16]), "+f"(d[17]), "+f"(d[18]), "+f"(d[19]), "+f"(d[20]), "+f"(d[21]), "+f"(d[22]), "+f"(d[23]), "+f"(d[24]), "+f"(d[25]), "+f"(d[26]), "+f"(d[27]), "+f"(d[28]), "+f"(d[29]), "+f"(d[30]), "+f"(d[31]), "+f"(d[32]), "+f"(d[33]), "+f"(d[34]), "+f"(d[35]), "+f"(d[36]), "+f"(d[37]), "+f"(d[38]), "+f"(d[39]), "+f"(d[40]), "+f"(d[41]), "+f"(d[42]), "+f"(d[43]), "+f"(d[44]), "+f"(d[45]), "+f"(d[46]), "+f"(d[47]), "+f"(d[48]), "+f"(d[49]), "+f"(d[50]), "+f"(d[51]), "+f"(d[52]), "+f"(d[53]), "+f"(d[54]), "+f"(d[55]), "+f"(d[56]), "+f"(d[57]), "+f"(d[58]), "+f"(d[59]), "+f"(d[60]), "+f"(d[61]), "+f"(d[62]), "+f"(d[63]) : "r"(a0), "r"(a1), "r"(a2), "r"(a3), "l"(db));
}
__device__ __forceinline__ void cw96(float (&d)[48], uint32_t a0, uint32_t a1, uint32_t a2, uint32_t a3, uint64_t db) {
  asm volatile("wgmma.mma_async.sync.aligned.m64n96k16.f32.bf16.bf16 {%0, %1, %2, %3, %4, %5, %6, %7, %8, %9, %10, %11, %12, %13, %14, %15, %16, %17, %18, %19, %20, %21, %22, %23, %24, %25, %26, %27, %28, %29, %30, %31, %32, %33, %34, %35, %36, %37, %38, %39, %40, %41, %42, %43, %44, %45, %46, %47}, {%48,%49,%50,%51}, %52, 1, 1, 1, 0;"
    : "+f"(d[0]), "+f"(d[1]), "+f"(d[2]), "+f"(d[3]), "+f"(d[4]), "+f"(d[5]), "+f"(d[6]), "+f"(d[7]), "+f"(d[8]), "+f"(d[9]), "+f"(d[10]), "+f"(d[11]), "+f"(d[12]), "+f"(d[13]), "+f"(d[14]), "+f"(d[15]), "+f"(d[16]), "+f"(d[17]), "+f"(d[18]), "+f"(d[19]), "+f"(d[20]), "+f"(d[21]), "+f"(d[22]), "+f"(d[23]), "+f"(d[24]), "+f"(d[25]), "+f"(d[26]), "+f"(d[27]), "+f"(d[28]), "+f"(d[29]), "+f"(d[30]), "+f"(d[31]), "+f"(d[32]), "+f"(d[33]), "+f"(d[34]), "+f"(d[35]), "+f"(d[36]), "+f"(d[37]), "+f"(d[38]), "+f"(d[39]), "+f"(d[40]), "+f"(d[41]), "+f"(d[42]), "+f"(d[43]), "+f"(d[44]), "+f"(d[45]), "+f"(d[46]), "+f"(d[47]) : "r"(a0), "r"(a1), "r"(a2), "r"(a3), "l"(db));
}
__device__ __forceinline__ void cw64(float (&d)[32], uint32_t a0, uint32_t a1, uint32_t a2, uint32_t a3, uint64_t db) {
  asm volatile("wgmma.mma_async.sync.aligned.m64n64k16.f32.bf16.bf16 {%0, %1, %2, %3, %4, %5, %6, %7, %8, %9, %10, %11, %12, %13, %14, %15, %16, %17, %18, %19, %20, %21, %22, %23, %24, %25, %26, %27, %28, %29, %30, %31}, {%32,%33,%34,%35}, %36, 1, 1, 1, 0;"
    : "+f"(d[0]), "+f"(d[1]), "+f"(d[2]), "+f"(d[3]), "+f"(d[4]), "+f"(d[5]), "+f"(d[6]), "+f"(d[7]), "+f"(d[8]), "+f"(d[9]), "+f"(d[10]), "+f"(d[11]), "+f"(d[12]), "+f"(d[13]), "+f"(d[14]), "+f"(d[15]), "+f"(d[16]), "+f"(d[17]), "+f"(d[18]), "+f"(d[19]), "+f"(d[20]), "+f"(d[21]), "+f"(d[22]), "+f"(d[23]), "+f"(d[24]), "+f"(d[25]), "+f"(d[26]), "+f"(d[27]), "+f"(d[28]), "+f"(d[29]), "+f"(d[30]), "+f"(d[31]) : "r"(a0), "r"(a1), "r"(a2), "r"(a3), "l"(db));
}
__device__ __forceinline__ void cw32(float (&d)[16], uint32_t a0, uint32_t a1, uint32_t a2, uint32_t a3, uint64_t db) {
  asm volatile("wgmma.mma_async.sync.aligned.m64n32k16.f32.bf16.bf16 {%0, %1, %2, %3, %4, %5, %6, %7, %8, %9, %10, %11, %12, %13, %14, %15}, {%16,%17,%18,%19}, %20, 1, 1, 1, 0;"
    : "+f"(d[0]), "+f"(d[1]), "+f"(d[2]), "+f"(d[3]), "+f"(d[4]), "+f"(d[5]), "+f"(d[6]), "+f"(d[7]), "+f"(d[8]), "+f"(d[9]), "+f"(d[10]), "+f"(d[11]), "+f"(d[12]), "+f"(d[13]), "+f"(d[14]), "+f"(d[15]) : "r"(a0), "r"(a1), "r"(a2), "r"(a3), "l"(db));
}

struct cpx { float r, i; };
__device__ __forceinline__ cpx cmul(cpx a, cpx b) { return {fmaf(a.r, b.r, -a.i * b.i), fmaf(a.r, b.i, a.i * b.r)}; }
__device__ __forceinline__ cpx csqr(cpx a) { return {fmaf(a.r, a.r, -a.i * a.i), (a.r * a.i) * 2.f}; }
__device__ __forceinline__ cpx cmulc(cpx a, cpx b) { return {fmaf(a.r, b.r, -a.i * b.i), fmaf(-a.r, b.i, -a.i * b.r)}; }
__device__ __forceinline__ cpx cexp_fast(float re, float im) {
  float e;
  asm("ex2.approx.ftz.f32 %0, %1;" : "=f"(e) : "f"(re * 1.4426950408889634f));
  float k = rintf(im * 0.15915494309189535f);
  float r = fmaf(k, -6.2831854820251465f, im);
  r = fmaf(k, 1.7484555314695172e-07f, r);
  float s, c;
  asm("sin.approx.f32 %0, %1;" : "=f"(s) : "f"(r));
  asm("cos.approx.f32 %0, %1;" : "=f"(c) : "f"(r));
  return {e * c, e * s};
}

struct KOps { uint32_t xa[5], xb[5], y[4]; };
__device__ __forceinline__ void kgen_ops(KOps& o, const float4 pr, const float2 qq, const float gf) {
  const cpx C = {pr.z, pr.w};
  const cpx Q = {qq.x, qq.y};
  const cpx V0 = cexp_fast(pr.x * gf, pr.y * gf);
  const cpx V1 = csqr(V0), V2 = csqr(V1), V3 = csqr(V2);
  const cpx Y0 = cmulc(C, V0), Y1 = cmulc(C, V1), Y2 = cmulc(C, V2), Y3 = cmulc(C, V3);
  o.y[0] = pack_f16(Y0.r, Y0.i); o.y[1] = pack_f16(Y1.r, Y1.i); o.y[2] = pack_f16(Y2.r, Y2.i); o.y[3] = pack_f16(Y3.r, Y3.i);
  const cpx Xb = cmul(V3, Q);
  cpx Xc = cmul(Xb, Q), Xd = cmul(Xc, Q);
  o.xa[0] = pack_f16(V3.r, V3.i); o.xb[0] = pack_f16(Xb.r, Xb.i);
  o.xa[1] = pack_f16(Xc.r, Xc.i); o.xb[1] = pack_f16(Xd.r, Xd.i);
#pragma unroll
  for (int k = 2; k < 5; k++) {
    Xc = csqr(Xc); Xd = csqr(Xd);
    o.xa[k] = pack_f16(Xc.r, Xc.i); o.xb[k] = pack_f16(Xd.r, Xd.i);
  }
}
__device__ __forceinline__ void kgen_mma(float (&T)[5][4], const KOps& a, const KOps& b) {
  asm("mma.sync.aligned.m16n8k16.row.col.f32.f16.f16.f32 {%0,%1,%2,%3}, {%20,%21,%22,%23}, {%40,%41}, {%0,%1,%2,%3};\n"
      "mma.sync.aligned.m16n8k16.row.col.f32.f16.f16.f32 {%4,%5,%6,%7}, {%24,%25,%26,%27}, {%40,%41}, {%4,%5,%6,%7};\n"
      "mma.sync.aligned.m16n8k16.row.col.f32.f16.f16.f32 {%8,%9,%10,%11}, {%28,%29,%30,%31}, {%42,%43}, {%8,%9,%10,%11};\n"
      "mma.sync.aligned.m16n8k16.row.col.f32.f16.f16.f32 {%12,%13,%14,%15}, {%32,%33,%34,%35}, {%44,%45}, {%12,%13,%14,%15};\n"
      "mma.sync.aligned.m16n8k16.row.col.f32.f16.f16.f32 {%16,%17,%18,%19}, {%36,%37,%38,%39}, {%46,%47}, {%16,%17,%18,%19};\n"
      : "+f"(T[0][0]), "+f"(T[0][1]), "+f"(T[0][2]), "+f"(T[0][3]), "+f"(T[1][0]), "+f"(T[1][1]), "+f"(T[1][2]), "+f"(T[1][3]),
        "+f"(T[2][0]), "+f"(T[2][1]), "+f"(T[2][2]), "+f"(T[2][3]), "+f"(T[3][0]), "+f"(T[3][1]), "+f"(T[3][2]), "+f"(T[3][3]),
        "+f"(T[4][0]), "+f"(T[4][1]), "+f"(T[4][2]), "+f"(T[4][3])
      : "r"(a.xa[0]), "r"(a.xb[0]), "r"(b.xa[0]), "r"(b.xb[0]), "r"(a.xa[1]), "r"(a.xb[1]), "r"(b.xa[1]), "r"(b.xb[1]),
        "r"(a.xa[2]), "r"(a.xb[2]), "r"(b.xa[2]), "r"(b.xb[2]), "r"(a.xa[3]), "r"(a.xb[3]), "r"(b.xa[3]), "r"(b.xb[3]),
        "r"(a.xa[4]), "r"(a.xb[4]), "r"(b.xa[4]), "r"(b.xb[4]),
        "r"(a.y[0]), "r"(b.y[0]), "r"(a.y[1]), "r"(b.y[1]), "r"(a.y[2]), "r"(b.y[2]), "r"(a.y[3]), "r"(b.y[3]));
}

template <int J0> __device__ __forceinline__ void conv_load4(uint32_t (&f)[4][4], uint32_t ebase, uint32_t zero) {
#pragma unroll
  for (int t = 0; t < 4; t++) {
    f[t][0] = lds32(ebase + (J0 + t) * 128);
    f[t][1] = lds32(ebase + (J0 + t) * 128 + 16);
    f[t][3] = lds32(ebase + (J0 + t) * 128 + 32);
  }
#pragma unroll
  for (int t = 0; t < 4; t++) f[t][2] = f[t][1] ^ zero;
}
#define CONV_GRP(FN, ACC, J0, F)                                                             \
  wg_fence();                                                                                \
  FN(ACC, F[0][0], F[0][1], F[0][2], F[0][3], de + 4 * (J0));                                \
  FN(ACC, F[1][0], F[1][1], F[1][2], F[1][3], de + 4 * (J0 + 1));                            \
  FN(ACC, F[2][0], F[2][1], F[2][2], F[2][3], de + 4 * (J0 + 2));                            \
  FN(ACC, F[3][0], F[3][1], F[3][2], F[3][3], de + 4 * (J0 + 3));                            \
  wg_commit();
#define CONV_STAGE(ACC, M0)                                                                  \
  _Pragma("unroll") for (int m = (M0); m < (M0) + 4; m++) {                                  \
    *(float2*)(Sw + 8 * m) = make_float2(ACC[4 * m], ACC[4 * m + 1]);                        \
    *(float2*)(Sw + 8 * S_PITCH + 8 * m) = make_float2(ACC[4 * m + 2], ACC[4 * m + 3]);      \
  }
#define CONV_CHANNEL(PRE, MID1, MID2)                                                                    \
  {                                                                                          \
    float a128[64], a96[48], a64[32], a32[16];                                               \
    wg_fence();                                                                              \
    cw128z(a128, fa[0][0], fa[0][1], fa[0][2], fa[0][3], de);                                \
    cw128(a128, fa[1][0], fa[1][1], fa[1][2], fa[1][3], de + 4);                             \
    cw128(a128, fa[2][0], fa[2][1], fa[2][2], fa[2][3], de + 8);                             \
    cw128(a128, fa[3][0], fa[3][1], fa[3][2], fa[3][3], de + 12);                            \
    wg_commit();                                                                             \
    CONV_GRP(cw128, a128, 4, fb)                                                             \
    MID1                                                                                     \
    wg_wait<1>(); conv_load4<8>(fa, ebase, zero);                                            \
    wg_wait<0>(); conv_load4<12>(fb, ebase, zero);                                           \
    _Pragma("unroll") for (int i = 0; i < 48; i++) movf(a96[i], a128[i]);                       \
    CONV_GRP(cw96, a96, 8, fa)                                                               \
    CONV_GRP(cw96, a96, 12, fb)                                                              \
    MID2                                                                                     \
    PRE                                                                                      \
    CONV_STAGE(a128, 12)                                                                     \
    wg_wait<1>(); conv_load4<16>(fa, ebase, zero);                                           \
    wg_wait<0>(); conv_load4<20>(fb, ebase, zero);                                           \
    _Pragma("unroll") for (int i = 0; i < 32; i++) movf(a64[i], a96[i]);                        \
    CONV_GRP(cw64, a64, 16, fa)                                                              \
    CONV_GRP(cw64, a64, 20, fb)                                                              \
    CONV_STAGE(a96, 8)                                                                       \
    wg_wait<1>(); conv_load4<24>(fa, ebase, zero);                                           \
    wg_wait<0>(); conv_load4<28>(fb, ebase, zero);                                           \
    _Pragma("unroll") for (int i = 0; i < 16; i++) movf(a32[i], a64[i]);                        \
    CONV_GRP(cw32, a32, 24, fa)                                                              \
    CONV_GRP(cw32, a32, 28, fb)                                                              \
    CONV_STAGE(a64, 4)                                                                       \
    load_u(ch);                                                                              \
    wg_wait<0>();                                                                            \
    CONV_STAGE(a32, 0)                                                                       \
  }

template <int V> struct IC { static constexpr int value = V; };

struct Params {
  const __nv_bfloat16* x;
  const __nv_bfloat16* log_A_real;
  const __nv_bfloat16* A_imag;
  const __nv_bfloat16* C_real;
  const __nv_bfloat16* C_imag;
  const __nv_bfloat16* log_dt;
  const __nv_bfloat16* D_skip;
  const __nv_bfloat16* gate_w;
  const __nv_bfloat16* w_gate;
  const __nv_bfloat16* w_up;
  const __nv_bfloat16* w_down;
  __nv_bfloat16* out;
};

struct Maps {
  CUtensorMap X, Wg, Wu, Wg3[2], Wu3[2], Wd, AT;
};

__device__ __forceinline__ uint32_t ld_epoch() { return *(volatile uint32_t*)&g_epoch; }
__device__ __forceinline__ uint32_t dup_lo(uint32_t w) { return __byte_perm(w, w, 0x1010); }
__device__ __forceinline__ uint32_t dup_hi(uint32_t w) { return __byte_perm(w, w, 0x3232); }

__global__ void __launch_bounds__(NTHREADS, 1)
fused_kernel(const __grid_constant__ Maps M, const Params P) {
  extern __shared__ __align__(1024) uint8_t smem[];
  const uint32_t sb = smem_u32(smem);
  const uint32_t bars = sb + SM_BAR;
  const int tid = threadIdx.x;
  const int warp = __shfl_sync(0xffffffffu, tid >> 5, 0), lane = tid & 31;
  const int b = blockIdx.x;
  const int cl = b >> 1;
  const int jf = cl & 7;
  const int it_ = ((cl >> 3) << 1) | (b & 1);
  const int d0 = b * 4;

  const int kch = warp / 3, kpart = warp - 3 * kch;
  const int kk0 = kpart == 0 ? 0 : (kpart == 1 ? 6 : 11), nks = kpart == 0 ? 6 : 5;
  uint32_t pw0[2], pw1[2], pldt;
#pragma unroll
  for (int r = 0; r < 2; r++) {
    int n = 8 * kk0 + lane + 32 * r;
    n = (d0 + kch) * NS_ + (n < NS_ ? n : NS_ - 1);
    pw0[r] = (uint32_t)*(const unsigned short*)(P.log_A_real + n) | ((uint32_t)*(const unsigned short*)(P.A_imag + n) << 16);
    pw1[r] = (uint32_t)*(const unsigned short*)(P.C_real + n) | ((uint32_t)*(const unsigned short*)(P.C_imag + n) << 16);
  }
  pldt = *(const unsigned short*)(P.log_dt + d0 + kch);
  if (lane == 0) {
#pragma unroll
    for (int r = 0; r < 5; r++) {
      const int i = warp + 12 * r;
      uint32_t cnt = 1;
      if ((i >= B_EMPTY && i < B_EMPTY + 5) || (i >= B_XFREE && i < B_XFREE + 8) || (i >= B_SENT && i < B_SENT + 8) || i == B_ADONE) cnt = 8;
      if (i == B_RRDY || i == B_KSUM) cnt = 2;
      if (i == B_KPART) cnt = 12;
      if (i == B_GOT) cnt = 7;
      mbar_init(bars + 8 * i, cnt);
    }
    asm volatile("fence.mbarrier_init.release.cluster;" ::: "memory");
  }
  TM_IF(tid == 0, 20);
  __syncthreads();
  TM_IF(tid == 0, 21);

  auto issue_stage = [&](int s, int slot) {
    const uint32_t dst = sb + SM_RING + slot * 16384;
    const uint32_t fb = bars + 8 * (B_FULL + slot);
    if (s < 32) {
      const int f0 = jf * 224 + ((s >> 4) << 7);
      const int k0 = (s & 15) * 32;
      mbar_expect(fb, 16384);
      if (jf == 7 && s >= 16) {
        tma2d(dst, &M.Wg, f0, k0, fb);
        tma2d(dst + 4096, &M.Wg, f0 + 64, k0, fb);
        tma2d(dst + 8192, &M.Wu, f0, k0, fb);
        tma2d(dst + 12288, &M.Wu, f0 + 64, k0, fb);
      } else {
        tma3d(dst, &M.Wg3[jf & 1], 0, k0, f0 >> 6, fb);
        tma3d(dst + 8192, &M.Wu3[jf & 1], 0, k0, f0 >> 6, fb);
      }
    } else {
      const int s2 = s - 32;
      const int p = (jf + 1 + (s2 >> 1)) & 7;
      mbar_expect(fb, 14336);
      tma2d(dst, &M.Wd, p * 64, jf * 224 + (s2 & 1) * 112, fb);
    }
  };
  auto issue_x = [&](int kb) {
    mbar_expect(bars + 8 * (B_XFULL + kb), 16384);
    tma2d(sb + SM_X + kb * 16384, &M.X, kb * 64, it_ * 128, bars + 8 * (B_XFULL + kb));
  };
  {
    const int g = lane >> 2, q = lane & 3;
    const float dtf = bf16r(expf(bf_lo(pldt)));
    const int pro = kch * 128 + 8 * kk0;
    float4* prm = (float4*)(smem + SM_PR) + pro;
    float2* prq = (float2*)(smem + SM_PR + 512 * 16) + pro;
    const bool valid1 = lane + 32 < 8 * nks;
    float m0 = fmaxf(fmaxf(fabsf(bf_lo(pw1[0])), fabsf(bf_hi(pw1[0]))), fmaxf(fabsf(bf_lo(pw1[1])), fabsf(bf_hi(pw1[1])))) * dtf;
#pragma unroll
    for (int o = 16; o > 0; o >>= 1) m0 = fmaxf(m0, __shfl_xor_sync(0xffffffffu, m0, o));
    TM_IF(tid == 0 && m0 >= 0.f, 0);
    if (m0 >= 0.f || m0 != m0) {
      if (tid == 256) {
        issue_x(0); issue_stage(0, 0); issue_stage(2, 2); issue_x(2); issue_stage(4, 4); issue_x(4);
      } else if (tid == 288) {
        issue_stage(1, 1); issue_x(1); issue_stage(3, 3); issue_x(3); issue_x(5);
      }
    }
    __syncwarp();
    const uint32_t e0 = min(max(__float_as_uint(m0) >> 23, 1u), 253u);
    const float sc = __uint_as_float((254u - e0) << 23);
    const float us = 2.f * __uint_as_float(e0 << 23);
    float pe = 0.f;
#pragma unroll
    for (int r = 0; r < 2; r++) {
      float4 v;
      v.x = -bf16r(expf(bf_lo(pw0[r]))) * dtf;
      v.y = bf_hi(pw0[r]) * dtf;
      v.z = bf_lo(pw1[r]) * dtf * sc;
      v.w = bf_hi(pw1[r]) * dtf * sc;
      const cpx Q = cexp_fast(v.x * 64.f, v.y * 64.f);
      const cpx We = cexp_fast(v.x * 2048.f, v.y * 2048.f);
      if (r == 0 || valid1) {
        pe += v.z * We.r - v.w * We.i;
        prm[lane + 32 * r] = v;
        prq[lane + 32 * r] = make_float2(Q.r, Q.i);
      }
    }
#pragma unroll
    for (int o = 16; o > 0; o >>= 1) pe += __shfl_xor_sync(0xffffffffu, pe, o);
    __syncwarp();
    TM_IF(tid == 0, 1);
    float T[5][4];
#pragma unroll
    for (int i = 0; i < 20; i++) T[i >> 2][i & 3] = 0.f;
    const float gf = (float)g;
#pragma unroll 1
    for (int ks = 0; ks < nks; ks++) {
      KOps o1, o2;
      kgen_ops(o1, prm[8 * ks + q], prq[8 * ks + q], gf);
      kgen_ops(o2, prm[8 * ks + 4 + q], prq[8 * ks + 4 + q], gf);
      kgen_mma(T, o1, o2);
    }
    float* kp = (float*)(smem + SM_X + 6 * 16384) + warp * KC_STRIDE + 8 * g + 2 * q;
#pragma unroll
    for (int k = 0; k < 5; k++) {
      *(float2*)(kp + 128 * k) = make_float2(T[k][0] * us, T[k][1] * us);
      *(float2*)(kp + 128 * k + 64) = make_float2(T[k][2] * us, T[k][3] * us);
    }
    if (lane == 0) { kp[640] = pe * us; kp[641] = 0.f; }
    TM_IF(tid == 0, 2);
    __syncwarp();
    if (lane == 0) mbar_arrive(bars + 8 * B_KPART);
  }

  if (warp >= 8) {
    asm volatile("setmaxnreg.dec.sync.aligned.u32 104;");
    if (warp < 10) {
      if (lane == 0) {
        int slot = (warp == 8) ? 1 : 0;
        uint32_t ph = 0;
#pragma unroll 1
        for (int s = (warp == 8) ? 6 : 5; s < 48; s += 2) {
          if (s == 10) { mbar_wait(bars + 8 * B_KSUM, 0); issue_x(6); issue_x(7); }
          mbar_wait(bars + 8 * (B_EMPTY + slot), ph);
          issue_stage(s, slot);
          slot += 2;
          if (slot >= 5) { slot -= 5; ph ^= 1; }
        }
      }
      __syncwarp();
      {
        const uint4 gw0 = *(const uint4*)(P.gate_w + lane * 16);
        const uint4 gw1 = *(const uint4*)(P.gate_w + lane * 16 + 8);
        uint4 xa[8], xb[8];
#pragma unroll
        for (int i = 0; i < 8; i++) {
          xa[i] = *(const uint4*)(P.x + (b * 16 + (warp - 8) * 8 + i) * D_ + lane * 16);
          xb[i] = *(const uint4*)(P.x + (b * 16 + (warp - 8) * 8 + i) * D_ + lane * 16 + 8);
        }
        float sg[8];
#pragma unroll
        for (int i = 0; i < 8; i++) {
          const uint32_t pr[8] = {hmul2_bf16(xa[i].x, gw0.x), hmul2_bf16(xa[i].y, gw0.y), hmul2_bf16(xa[i].z, gw0.z), hmul2_bf16(xa[i].w, gw0.w),
                                  hmul2_bf16(xb[i].x, gw1.x), hmul2_bf16(xb[i].y, gw1.y), hmul2_bf16(xb[i].z, gw1.z), hmul2_bf16(xb[i].w, gw1.w)};
          float s = 0.f;
#pragma unroll
          for (int k = 0; k < 8; k++) s += bf_lo(pr[k]) + bf_hi(pr[k]);
          sg[i] = s;
        }
#pragma unroll
        for (int o = 16; o > 0; o >>= 1) {
#pragma unroll
          for (int i = 0; i < 8; i++) sg[i] += __shfl_xor_sync(0xffffffffu, sg[i], o);
        }
        float z = sg[0];
#pragma unroll
        for (int i = 1; i < 8; i++) z = (lane == i) ? sg[i] : z;
        if (lane < 8) g_gate[b * 16 + (warp - 8) * 8 + lane] = bf16r(1.f / (1.f + expf(-bf16r(z))));
      }
      bar_sync(3, 64);
      if (tid == 288) asm volatile("red.release.gpu.global.add.u32 [%0], 1;" ::"l"(&g_done1) : "memory");
      TM_IF(tid == 256, 16);
      if (warp == 8) {
        if (lane >= 1 && lane < 8) {
          const uint32_t tag = ld_epoch() + 1;
          const uint32_t* fp = g_flag + ((it_ * 8 + jf) * 8 + ((jf - lane) & 7));
          int itc = 0;
          while (ld_acquire(fp) != tag) { __nanosleep(100); if (++itc > SPIN_LIMIT) FAIL(-2, lane); }
          mbar_arrive(bars + 8 * B_GOT);
          TM_IF(lane == 7, 25);
        }
      } else if (lane == 0) {
        const uint32_t tag = ld_epoch() + 1;
#pragma unroll 1
        for (int rnd = 0; rnd < 2; rnd++) {
          if (rnd == 1) {
            int itc = 0;
            while ((int)(ld_acquire(&g_done1) - (uint32_t)NCTA * tag) < 0) { if (++itc > SPIN_LIMIT) FAIL(-1, 0); }
            mbar_wait(bars + 8 * B_ADONE, 1);
          } else {
            mbar_wait_lazy<100>(bars + 8 * B_ADONE, 0);
          }
          TM_IF(true, 24);
#pragma unroll
          for (int v = 0; v < 2; v++)
            asm volatile("cp.async.bulk.global.shared::cta.bulk_group [%0], [%1], %2;"
                         ::"l"(g_aT + (d0 + 2 * v + rnd) * L_), "r"(sb + SM_X + CV_R + (2 * v + rnd) * R_CH), "r"(4096) : "memory");
          asm volatile("cp.async.bulk.commit_group;" ::: "memory");
          asm volatile("cp.async.bulk.wait_group 0;" ::: "memory");
          asm volatile("red.relaxed.gpu.global.add.u32 [%0], 1;" ::"l"(g_cnt + 32 * (b >> 4)) : "memory");
        }
        TM_IF(true, 26);
        {
          int itc = 0;
          while ((int)(ld_acquire(g_cnt + 32 * jf) - 32u * tag) < 0) { if (++itc > SPIN_LIMIT) FAIL(-3, 0); }
        }
        TM_IF(true, 23);
        asm volatile("fence.proxy.async.global;" ::: "memory");
        mbar_expect(bars + 8 * B_ATILE, 16384);
        tma2d(sb + SM_AT, &M.AT, it_ * 128, jf * 64, bars + 8 * B_ATILE);
        tma2d(sb + SM_AT + 8192, &M.AT, it_ * 128 + 64, jf * 64, bars + 8 * B_ATILE);
      }
      __syncwarp();
    } else {
      const int w = warp - 10;
      const int wt = tid - 320;
      mbar_wait(bars + 8 * B_KPART, 0);
      {
        const float2* kp = (const float2*)(smem + SM_X + 6 * 16384);
        uint32_t* kb = (uint32_t*)(smem + SM_KB);
#pragma unroll
        for (int ch = 0; ch < 4; ch++) {
#pragma unroll
          for (int i = 0; i < 6; i++) {
            const int o = wt + 64 * i;
            if (i < 5 || o < 321) {
              const float2 a0 = kp[(3 * ch) * (KC_STRIDE / 2) + o], a1 = kp[(3 * ch + 1) * (KC_STRIDE / 2) + o], a2 = kp[(3 * ch + 2) * (KC_STRIDE / 2) + o];
              kb[ch * (KC_STRIDE / 2) + o] = pack_bf16(a0.x + a1.x + a2.x, a0.y + a1.y + a2.y);
            }
          }
        }
      }
      __syncwarp();
      if (lane == 0) mbar_arrive(bars + 8 * B_KSUM);
      {
        const uint32_t zz = *(volatile uint32_t*)&g_zero;
        uint2 ur[4][8];
#pragma unroll
        for (int i = 0; i < 4; i++) {
#pragma unroll
          for (int r = 0; r < 8; r++) {
            uint32_t ck;
            asm volatile("nanosleep.u32 120;\n\tmov.u32 %0, %%clock;" : "=r"(ck) :: "memory");
            asm volatile("ld.global.nc.v2.u32 {%0,%1}, [%2];" : "=r"(ur[i][r].x), "=r"(ur[i][r].y)
                         : "l"(P.x + ((wt + 64 * i) * 8 + r) * D_ + d0 + (ck & zz)));
          }
        }
        mbar_wait_lazy<200>(bars + 8 * (B_XFREE + 7), 0);
        TM_IF(wt == 0, 18);
#pragma unroll
        for (int i = 0; i < 4; i++) {
          const int item = wt + 64 * i;
          const int c = item >> 1, hh = item & 1;
#pragma unroll
          for (int ch = 0; ch < 4; ch++) {
            uint32_t v[4];
#pragma unroll
            for (int k = 0; k < 4; k++) {
              const uint32_t lo = (ch < 2) ? ur[i][7 - 2 * k].x : ur[i][7 - 2 * k].y;
              const uint32_t hi = (ch < 2) ? ur[i][6 - 2 * k].x : ur[i][6 - 2 * k].y;
              v[k] = (ch & 1) ? __byte_perm(lo, hi, 0x7632) : __byte_perm(lo, hi, 0x5410);
            }
            *(uint4*)(smem + SM_X + CV_R + ch * R_CH + (1 - hh) * R_HALF + (127 - c) * 16) = make_uint4(v[0], v[1], v[2], v[3]);
          }
        }
        if (lane < 28) {
#pragma unroll
          for (int z = 0; z < 4; z++)
            *(uint4*)(smem + SM_X + CV_R + (4 * w + z) * R_HALF + (128 + lane) * 16) = make_uint4(0, 0, 0, 0);
        }
      }
      auto part_store = [&](int s) {
        mbar_wait_lazy<100>(bars + 8 * (B_SENT + s), 0);
        const int fi = (it_ * 8 + ((jf + 1 + s) & 7)) * 8 + jf;
#pragma unroll
        for (int v = 0; v < 2; v++)
          asm volatile("cp.async.bulk.global.shared::cta.bulk_group [%0], [%1], %2;"
                       ::"l"(g_part + (size_t)fi * 1024 + v * 512), "r"(sb + SM_X + (s == 6 ? CV_E + 2 * v * E_CH : CV_S + v * S_WG + (s & 3) * 8192)), "r"(8192) : "memory");
        asm volatile("cp.async.bulk.commit_group;" ::: "memory");
      };
      if (w == 0 && lane == 0) part_store(0);
      __syncwarp();
      {
#pragma unroll 1
      for (int G = w; G < 8; G += 2) {
        const int n = 32 * G + lane;
        uint4 c0[4], c1[4];
        if (G >= 4) {
#pragma unroll
          for (int ch = 0; ch < 4; ch++) {
            const uint8_t* kc = smem + SM_KB + ch * KC_STRIDE * 2;
            const uint32_t a = *(const unsigned short*)(kc + (384 + n) * 2), bb = *(const unsigned short*)(kc + (385 + n) * 2);
            const uint32_t aa = a | (a << 16), b2 = bb | (bb << 16);
            const uint32_t tie = (n & 1) ? bb : a;
            c0[ch] = make_uint4(aa, a | (tie << 16), b2, b2);
            c1[ch] = make_uint4(aa, tie | (bb << 16), b2, b2);
          }
        } else if (G >= 2) {
#pragma unroll
          for (int ch = 0; ch < 4; ch++) {
            const uint8_t* kc = smem + SM_KB + ch * KC_STRIDE * 2;
            const uint32_t w0 = *(const uint32_t*)(kc + (256 + 2 * n) * 2), w1 = *(const uint32_t*)(kc + (258 + 2 * n) * 2);
            c0[ch] = make_uint4(dup_lo(w0), dup_hi(w0), __byte_perm(w0, w1, 0x5432), dup_lo(w1));
            c1[ch] = make_uint4(w0, dup_hi(w0), dup_lo(w1), dup_lo(w1));
          }
        } else if (G == 1) {
#pragma unroll
          for (int ch = 0; ch < 4; ch++) {
            const uint8_t* kc = smem + SM_KB + ch * KC_STRIDE * 2;
            const uint2 w01 = *(const uint2*)(kc + (128 + 4 * n) * 2);
            const uint32_t w2 = *(const uint32_t*)(kc + (132 + 4 * n) * 2);
            c0[ch] = make_uint4(w01.x, dup_lo(w01.y), w01.y, dup_lo(w2));
            c1[ch] = make_uint4(__byte_perm(w01.x, w01.y, 0x5432), dup_lo(w01.y), __byte_perm(w01.y, w2, 0x5432), dup_lo(w2));
          }
        } else {
#pragma unroll
          for (int ch = 0; ch < 4; ch++) {
            const uint8_t* kc = smem + SM_KB + ch * KC_STRIDE * 2;
            const uint4 wv = *(const uint4*)(kc + (8 * n) * 2);
            const uint32_t w4 = *(const uint32_t*)(kc + (8 * n + 8) * 2);
            c0[ch] = make_uint4(__byte_perm(wv.x, wv.y, 0x5432), __byte_perm(wv.y, wv.z, 0x5432), __byte_perm(wv.z, wv.w, 0x5432), __byte_perm(wv.w, w4, 0x5432));
            c1[ch] = make_uint4(wv.y, wv.z, wv.w, (n == 31) ? dup_lo(w4) : w4);
          }
          if (lane < 8) {
            const int ch = lane >> 1, hi = lane & 1;
            const uint32_t k01 = *(const uint32_t*)(smem + SM_KB + ch * KC_STRIDE * 2);
            uint8_t* e = smem + SM_X + CV_E + ch * E_CH + hi * 16;
            *(uint4*)e = make_uint4(0, 0, 0, hi ? (k01 << 16) : 0u);
            *(uint4*)(e + E_COPY) = make_uint4(0, 0, 0, hi ? k01 : 0u);
          }
        }
#pragma unroll
        for (int ch = 0; ch < 4; ch++) {
          uint8_t* e = smem + SM_X + CV_E + ch * E_CH + (n + 2) * 16;
          *(uint4*)e = c0[ch];
          *(uint4*)(e + E_COPY) = c1[ch];
        }
      }
        fence_async();
        __syncwarp();
        if (lane == 0) mbar_arrive(bars + 8 * B_RRDY);
        TM_IF(wt == 0, 19);
      }
      if (lane == 0) {
        const uint32_t tag = ld_epoch() + 1;
        auto publish = [&](int s) {
          asm volatile("st.relaxed.gpu.global.u32 [%0], %1;" ::"l"(g_flag + ((it_ * 8 + ((jf + 1 + s) & 7)) * 8 + jf)), "r"(tag) : "memory");
          TM_IF(true, 3 + s);
        };
#pragma unroll 1
        for (int s = w; s < 7; s += 2) {
          if (s > 0) part_store(s);
          asm volatile("cp.async.bulk.wait_group.read 0;" ::: "memory");
          mbar_arrive(bars + 8 * (B_STF + s));
          if (s >= 2 && s < 6) {
            asm volatile("cp.async.bulk.wait_group 1;" ::: "memory");
            publish(s - 2);
          }
          if (s >= 4) {
            asm volatile("cp.async.bulk.wait_group 0;" ::: "memory");
            publish(s);
          }
        }
      }
      __syncwarp();
    }
    bar_sync(2, 128);
    if (tid == 256) {
      const uint32_t tk = atomicAdd(&g_exit, 1u);
      if (tk == NCTA - 1) {
        g_exit = 0;
        *(volatile uint32_t*)&g_epoch = ld_epoch() + 1;
      }
    }
    TM_IF(tid == 256, 13);
  } else {
    asm volatile("setmaxnreg.inc.sync.aligned.u32 200;");
    const int wg = warp >> 2;
    const int g = lane >> 2, q = lane & 3;
    const uint32_t dsk = *(const uint32_t*)(P.D_skip + d0 + 2 * wg);
    uint32_t hf[56];
    {
      float acc[128];
#pragma unroll
      for (int i = 0; i < 128; i++) zero_reg(acc[i]);
#pragma unroll 1
      for (int st = 0; st < 16; st++) {
        const int slot = st % 5;
        if ((st & 1) == 0) mbar_wait(bars + 8 * (B_XFULL + (st >> 1)), 0);
        mbar_wait(bars + 8 * (B_FULL + slot), (st / 5) & 1);
        const uint64_t da = mkdesc(sb + SM_X + (st >> 1) * 16384 + wg * 8192 + (st & 1) * 64, 16, 1024, 1);
        const uint64_t db = mkdesc(sb + SM_RING + slot * 16384, 4096, 1024, 1);
        wg_fence();
        wgmma_ss_n256(acc, da, db);
        wgmma_ss_n256(acc, da + 2, db + 128);
        wg_commit();
        if (st > 0) {
          wg_wait<1>();
          if (lane == 0) mbar_arrive(bars + 8 * (B_EMPTY + (st - 1) % 5));
        }
      }
      wg_wait<0>();
      if (lane == 0) mbar_arrive(bars + 8 * (B_EMPTY + 15 % 5));
#pragma unroll
      for (int m = 0; m < 16; m++) {
        hf[2 * m] = hmul2_bf16(pack_bf16(acc[4 * m], acc[4 * m + 1]), pack_bf16(acc[64 + 4 * m], acc[64 + 4 * m + 1]));
        hf[2 * m + 1] = hmul2_bf16(pack_bf16(acc[4 * m + 2], acc[4 * m + 3]), pack_bf16(acc[64 + 4 * m + 2], acc[64 + 4 * m + 3]));
      }
    }
    {
      float accg[48], accu[48];
#pragma unroll
      for (int i = 0; i < 48; i++) { zero_reg(accg[i]); zero_reg(accu[i]); }
      const uint32_t xrow = sb + SM_X + (wg * 64 + (warp & 3) * 16 + (lane & 15)) * 128;
      const uint32_t xsw = lane & 7, xhi = lane >> 4;
      uint32_t a0[4], a1[4], a2[4], a3[4];
#pragma unroll 1
      for (int kb = 0; kb < 8; kb++) {
        const uint32_t xb = xrow + kb * 16384;
        {
          const int st = 16 + 2 * kb, slot = st % 5;
          ldsm4(a0, xb + (((0 + xhi) ^ xsw) << 4));
          ldsm4(a1, xb + (((2 + xhi) ^ xsw) << 4));
          mbar_wait(bars + 8 * (B_FULL + slot), (st / 5) & 1);
          const uint64_t db = mkdesc(sb + SM_RING + slot * 16384, 4096, 1024, 1);
          wg_fence();
          wgmma_rs_n96(accg, a0[0], a0[1], a0[2], a0[3], db);
          wgmma_rs_n96(accu, a0[0], a0[1], a0[2], a0[3], db + 512);
          wgmma_rs_n96(accg, a1[0], a1[1], a1[2], a1[3], db + 128);
          wgmma_rs_n96(accu, a1[0], a1[1], a1[2], a1[3], db + 128 + 512);
          wg_commit();
          wg_wait<1>();
          if (kb > 0 && lane == 0) mbar_arrive(bars + 8 * (B_EMPTY + (st - 1) % 5));
        }
        {
          const int st = 17 + 2 * kb, slot = st % 5;
          ldsm4(a2, xb + (((4 + xhi) ^ xsw) << 4));
          ldsm4(a3, xb + (((6 + xhi) ^ xsw) << 4));
          mbar_wait(bars + 8 * (B_FULL + slot), (st / 5) & 1);
          const uint64_t db = mkdesc(sb + SM_RING + slot * 16384, 4096, 1024, 1);
          wg_fence();
          wgmma_rs_n96(accg, a2[0], a2[1], a2[2], a2[3], db);
          wgmma_rs_n96(accu, a2[0], a2[1], a2[2], a2[3], db + 512);
          wgmma_rs_n96(accg, a3[0], a3[1], a3[2], a3[3], db + 128);
          wgmma_rs_n96(accu, a3[0], a3[1], a3[2], a3[3], db + 128 + 512);
          wg_commit();
          wg_wait<1>();
          if (lane == 0) mbar_arrive(bars + 8 * (B_EMPTY + (st - 1) % 5));
        }
      }
      wg_wait<0>();
      if (lane == 0) { mbar_arrive(bars + 8 * (B_EMPTY + 31 % 5)); mbar_arrive(bars + 8 * (B_XFREE + 7)); }
#pragma unroll
      for (int m = 0; m < 12; m++) {
        hf[32 + 2 * m] = hmul2_bf16(pack_bf16(accg[4 * m], accg[4 * m + 1]), pack_bf16(accu[4 * m], accu[4 * m + 1]));
        hf[32 + 2 * m + 1] = hmul2_bf16(pack_bf16(accg[4 * m + 2], accg[4 * m + 3]), pack_bf16(accu[4 * m + 2], accu[4 * m + 3]));
      }
    }
    float accA[32], accB[32];
    auto issue_half = [&](float (&acc)[32], int s, auto half_tag) {
      constexpr int half = decltype(half_tag)::value;
      if (half == 0) {
#pragma unroll
        for (int i = 0; i < 32; i++) zero_reg(acc[i]);
      }
      const int st = 32 + 2 * s + half;
      const int slot = st % 5;
      mbar_wait(bars + 8 * (B_FULL + slot), (st / 5) & 1);
      uint32_t sbase;
      asm volatile("mov.b32 %0, %1;" : "=r"(sbase) : "r"(sb + SM_RING + slot * 16384));
      const uint64_t db = mkdesc(sbase, 1024, 1024, 1);
      wg_fence();
#pragma unroll
      for (int k = 0; k < 7; k++) {
        const int ks = 7 * half + k;
        wgmma_rs_n64t(acc, hf[4 * ks], hf[4 * ks + 1], hf[4 * ks + 2], hf[4 * ks + 3], db + k * 128);
      }
      wg_commit();
    };
    auto release = [&](int st) { if (lane == 0) mbar_arrive(bars + 8 * (B_EMPTY + st % 5)); };
    using H0 = IC<0>;
    using H1 = IC<1>;
    auto send_pass = [&](float (&acc)[32], int s) {
      uint4* dst = (uint4*)(smem + SM_X + (s == 6 ? CV_E + 2 * wg * E_CH : CV_S + wg * S_WG + (s & 3) * 8192) + (warp & 3) * 2048) + lane;
#pragma unroll
      for (int c = 0; c < 4; c++) {
        uint4 v;
        v.x = pack_bf16(acc[8 * c], acc[8 * c + 1]); v.y = pack_bf16(acc[8 * c + 2], acc[8 * c + 3]);
        v.z = pack_bf16(acc[8 * c + 4], acc[8 * c + 5]); v.w = pack_bf16(acc[8 * c + 6], acc[8 * c + 7]);
        dst[c * 32] = v;
      }
      fence_async();
      __syncwarp();
      if (lane == 0) mbar_arrive(bars + 8 * (B_SENT + s));
    };
    auto part_load = [&](uint4 (&v)[4], int k) {
      const uint4* sp = g_part + (size_t)(((it_ * 8 + jf) * 8 + ((jf - k) & 7)) * 8 + warp) * 128 + lane;
#pragma unroll
      for (int c = 0; c < 4; c++) v[c] = ld_cg4(sp + c * 32);
    };
    auto part_add = [&](const uint4 (&v)[4]) {
#pragma unroll
      for (int c = 0; c < 4; c++) {
        accA[8 * c] += bf_lo(v[c].x); accA[8 * c + 1] += bf_hi(v[c].x); accA[8 * c + 2] += bf_lo(v[c].y); accA[8 * c + 3] += bf_hi(v[c].y);
        accA[8 * c + 4] += bf_lo(v[c].z); accA[8 * c + 5] += bf_hi(v[c].z); accA[8 * c + 6] += bf_lo(v[c].w); accA[8 * c + 7] += bf_hi(v[c].w);
      }
    };
    mbar_wait(bars + 8 * (B_XFREE + 7), 0);
    issue_half(accA, 0, H0{});
    issue_half(accA, 0, H1{}); wg_wait<1>(); release(32);
    issue_half(accB, 1, H0{}); wg_wait<1>(); release(33); send_pass(accA, 0);
    issue_half(accB, 1, H1{}); wg_wait<1>(); release(34);
    issue_half(accA, 2, H0{}); wg_wait<1>(); release(35); send_pass(accB, 1);
    issue_half(accA, 2, H1{}); wg_wait<1>(); release(36);
    issue_half(accB, 3, H0{}); wg_wait<1>(); release(37); send_pass(accA, 2);
    issue_half(accB, 3, H1{}); wg_wait<1>(); release(38);
    issue_half(accA, 4, H0{}); wg_wait<1>(); release(39); send_pass(accB, 3);
    issue_half(accA, 4, H1{}); wg_wait<1>(); release(40);
    issue_half(accB, 5, H0{}); wg_wait<1>(); release(41); mbar_wait(bars + 8 * (B_STF + 0), 0); send_pass(accA, 4);
    issue_half(accB, 5, H1{}); wg_wait<1>(); release(42);
    wg_wait<0>(); mbar_wait(bars + 8 * (B_STF + 1), 0); send_pass(accB, 5);
    {
      TM_IF(tid == 0, 10);
      const int w = warp & 3;
      mbar_wait(bars + 8 * B_RRDY, 0);
      TM_IF(tid == 0, 11);
      const uint32_t zero = lds32(sb + SM_X + CV_R + 128 * 16);
      const int c = tid & 127;
      const float* Sr = (const float*)(smem + SM_X + CV_S + wg * S_WG) + (127 - c);
      float* Sw = (float*)(smem + SM_X + CV_S + wg * S_WG) + w * 16 * S_PITCH + g * S_PITCH + 2 * q;
      uint32_t fa[4][4], fb[4][4];
      uint32_t ares[8], rv[8];
      auto load_u = [&](int ch) {
        const uint4 r0v = *(const uint4*)(smem + SM_X + CV_R + ch * R_CH + (127 - c) * 16);
        const uint4 r1v = *(const uint4*)(smem + SM_X + CV_R + ch * R_CH + R_HALF + (127 - c) * 16);
        rv[0] = r0v.x; rv[1] = r0v.y; rv[2] = r0v.z; rv[3] = r0v.w; rv[4] = r1v.x; rv[5] = r1v.y; rv[6] = r1v.z; rv[7] = r1v.w;
      };
#define POST(r2, dk2)                                                                              \
      {                                                                                            \
        float y_[2];                                                                               \
        _Pragma("unroll") for (int t2 = 0; t2 < 2; t2++) {                                         \
          const int r0 = 2 * (r2) + t2;                                                            \
          const float s1 = c >= 1 ? Sr[(16 + r0) * S_PITCH + 1] : 0.f;                             \
          const float s2 = c >= 2 ? Sr[(32 + r0) * S_PITCH + 2] : 0.f;                             \
          const float s3 = c >= 3 ? Sr[(48 + r0) * S_PITCH + 3] : 0.f;                             \
          y_[t2] = (Sr[r0 * S_PITCH] + s1) + (s2 + s3);                                            \
        }                                                                                          \
        ares[r2] = hadd2_bf16(pack_bf16(y_[0], y_[1]), hmul2_bf16(__byte_perm(rv[7 - (r2)], rv[7 - (r2)], 0x1032), dk2)); \
      }
      auto store_a = [&](int ch) {
        uint4* ap = (uint4*)(smem + SM_X + CV_R + ch * R_CH + c * 32);
        ap[0] = make_uint4(ares[0], ares[1], ares[2], ares[3]);
        ap[1] = make_uint4(ares[4], ares[5], ares[6], ares[7]);
        fence_async();
      };
      const uint32_t eoff = ((g & 1) ? E_COPY : 0) + (16 * w + (g & ~1) + 2 * q) * 2;
      const uint32_t dkA = dup_lo(dsk), dkB = dup_hi(dsk);
      {
        const int ch = 2 * wg;
        const uint32_t ebase = sb + SM_X + CV_E + ch * E_CH + eoff;
        const uint64_t de = mkdesc(sb + SM_X + CV_R + ch * R_CH, R_HALF, 128, 0);
        conv_load4<0>(fa, ebase, zero);
        conv_load4<4>(fb, ebase, zero);
        CONV_CHANNEL(mbar_wait(bars + 8 * (B_STF + 2), 0); mbar_wait(bars + 8 * (B_STF + 3), 0); mbar_wait(bars + 8 * (B_STF + 4), 0); mbar_wait(bars + 8 * (B_STF + 5), 0);, , )
        TM_IF(tid == 0, 14);
      }
      issue_half(accA, 6, H0{});
      issue_half(accA, 6, H1{});
      bar_sync(6 + wg, 128);
      POST(0, dkA) POST(1, dkA) POST(2, dkA) POST(3, dkA) POST(4, dkA) POST(5, dkA) POST(6, dkA) POST(7, dkA)
      store_a(2 * wg);
      __syncwarp();
      if (lane == 0) mbar_arrive(bars + 8 * B_ADONE);
      {
        const int ch = 2 * wg + 1;
        const uint32_t ebase = sb + SM_X + CV_E + ch * E_CH + eoff;
        const uint64_t de = mkdesc(sb + SM_X + CV_R + ch * R_CH, R_HALF, 128, 0);
        conv_load4<0>(fa, ebase, zero);
        conv_load4<4>(fb, ebase, zero);
        wg_wait<0>();
        send_pass(accA, 6);
        CONV_CHANNEL(bar_sync(6 + wg, 128);, , )
        bar_sync(6 + wg, 128);
        TM_IF(tid == 0, 17);
        POST(0, dkB) POST(1, dkB) POST(2, dkB) POST(3, dkB) POST(4, dkB) POST(5, dkB) POST(6, dkB) POST(7, dkB)
        store_a(ch);
        __syncwarp();
        if (lane == 0) mbar_arrive(bars + 8 * B_ADONE);
      }
#undef POST
    }
    {
      uint4 v0[4], v1[4], v2[4], v3[4];
      mbar_wait(bars + 8 * B_GOT, 0);
      part_load(v0, 1);
      part_load(v1, 2);
      part_load(v2, 3);
      part_load(v3, 4);
      issue_half(accB, 7, H0{});
      issue_half(accB, 7, H1{});
#pragma unroll
      for (int i = 0; i < 32; i++) accA[i] = 0.f;
      part_add(v0); part_load(v0, 5);
      part_add(v1); part_load(v1, 6);
      part_add(v2); part_load(v2, 7);
      part_add(v3);
      part_add(v0);
      part_add(v1);
      part_add(v2);
    }
    TM_IF(tid == 0, 28);
    mbar_wait(bars + 8 * B_ATILE, 0);
    TM_IF(tid == 0, 29);
    const int row0 = it_ * 128 + warp * 16 + g;
    const float g0 = __ldcg(g_gate + row0), g1 = __ldcg(g_gate + row0 + 8);
    uint32_t av[16];
    {
      const int dl = (lane & 7) + ((lane >> 4) << 3);
      const int chunk = 2 * (warp & 3) + ((lane >> 3) & 1);
      const uint32_t abase = sb + SM_AT + wg * 8192 + dl * 128 + ((chunk ^ (lane & 7)) << 4);
#pragma unroll
      for (int m2 = 0; m2 < 4; m2++) {
        asm volatile("ldmatrix.sync.aligned.m8n8.x4.trans.shared.b16 {%0,%1,%2,%3}, [%4];"
                     : "=r"(av[4 * m2]), "=r"(av[4 * m2 + 1]), "=r"(av[4 * m2 + 2]), "=r"(av[4 * m2 + 3]) : "r"(abase + m2 * 2048) : "memory");
      }
    }
    wg_wait<0>();
    const uint32_t gg0 = pack_bf16(g0, g0), gg1 = pack_bf16(g1, g1);
    const uint32_t og0 = pack_bf16(1.f - g0, 1.f - g0), og1 = pack_bf16(1.f - g1, 1.f - g1);
    uint32_t ov[16];
#pragma unroll
    for (int m = 0; m < 8; m++) {
      const uint32_t b0 = pack_bf16(accA[4 * m] + accB[4 * m], accA[4 * m + 1] + accB[4 * m + 1]);
      const uint32_t b1 = pack_bf16(accA[4 * m + 2] + accB[4 * m + 2], accA[4 * m + 3] + accB[4 * m + 3]);
      ov[2 * m] = hadd2_bf16(hmul2_bf16(gg0, av[2 * m]), hmul2_bf16(og0, b0));
      ov[2 * m + 1] = hadd2_bf16(hmul2_bf16(gg1, av[2 * m + 1]), hmul2_bf16(og1, b1));
    }
    {
      const uint32_t ob = sb + SM_X + CV_S + wg * S_WG + (warp & 3) * 2048;
      const int srow = (lane & 7) + ((lane >> 3) & 1) * 8;
#pragma unroll
      for (int m2 = 0; m2 < 4; m2++) {
        const int chunk = 2 * m2 + (lane >> 4);
        asm volatile("stmatrix.sync.aligned.m8n8.x4.shared.b16 [%0], {%1,%2,%3,%4};"
                     ::"r"(ob + srow * 128 + ((chunk ^ (srow & 7)) << 4)), "r"(ov[4 * m2]), "r"(ov[4 * m2 + 1]), "r"(ov[4 * m2 + 2]), "r"(ov[4 * m2 + 3]) : "memory");
      }
      __syncwarp();
#pragma unroll
      for (int i = 0; i < 4; i++) {
        const int r = 4 * i + (lane >> 3), chunk = lane & 7;
        const uint4 v = *(const uint4*)(smem + SM_X + CV_S + wg * S_WG + (warp & 3) * 2048 + r * 128 + ((chunk ^ (r & 7)) << 4));
        *(uint4*)(P.out + (it_ * 128 + warp * 16 + r) * D_ + jf * 64 + chunk * 8) = v;
      }
    }
    TM_IF(tid == 0, 30);
  }
}

typedef CUresult (*EncFn)(CUtensorMap*, CUtensorMapDataType, cuuint32_t, void*, const cuuint64_t*, const cuuint64_t*, const cuuint32_t*,
                          const cuuint32_t*, CUtensorMapInterleave, CUtensorMapSwizzle, CUtensorMapL2promotion, CUtensorMapFloatOOBfill);

struct HostState {
  bool ready;
  const void* key[4];
  Maps M;
};
HostState hs;

}

extern "C" void kernel_launch(void* const* d_in, const int* in_sizes, int n_in, void* d_out, int out_size) {
  (void)in_sizes; (void)n_in; (void)out_size;
  void* x = d_in[0];
  void* wg = d_in[8];
  void* wu = d_in[9];
  void* wd = d_in[10];
  if (!hs.ready || hs.key[0] != x || hs.key[1] != wg || hs.key[2] != wu || hs.key[3] != wd) {
    void* fn = nullptr;
    cudaDriverEntryPointQueryResult qr;
    cudaGetDriverEntryPoint("cuTensorMapEncodeTiled", &fn, cudaEnableDefault, &qr);
    EncFn enc = (EncFn)fn;
    const cuuint32_t es[3] = {1, 1, 1};
    const CUtensorMapDataType BF = CU_TENSOR_MAP_DATA_TYPE_BFLOAT16;
    const CUtensorMapInterleave IN = CU_TENSOR_MAP_INTERLEAVE_NONE;
    const CUtensorMapL2promotion PR = CU_TENSOR_MAP_L2_PROMOTION_L2_128B;
    const CUtensorMapFloatOOBfill OO = CU_TENSOR_MAP_FLOAT_OOB_FILL_NONE;
    {
      cuuint64_t gd[2] = {(cuuint64_t)D_, (cuuint64_t)L_}; cuuint64_t gs[1] = {(cuuint64_t)D_ * 2}; cuuint32_t box[2] = {64, 128};
      enc(&hs.M.X, BF, 2, x, gd, gs, box, es, IN, CU_TENSOR_MAP_SWIZZLE_128B, PR, OO);
    }
    {
      cuuint64_t gd[2] = {(cuuint64_t)F_, (cuuint64_t)D_}; cuuint64_t gs[1] = {(cuuint64_t)F_ * 2}; cuuint32_t box[2] = {64, 32};
      enc(&hs.M.Wg, BF, 2, wg, gd, gs, box, es, IN, CU_TENSOR_MAP_SWIZZLE_128B, PR, OO);
      enc(&hs.M.Wu, BF, 2, wu, gd, gs, box, es, IN, CU_TENSOR_MAP_SWIZZLE_128B, PR, OO);
      for (int o = 0; o < 2; o++) {
        cuuint64_t gd3[3] = {64, (cuuint64_t)D_, (cuuint64_t)(F_ / 64 - o)}; cuuint64_t gs3[2] = {(cuuint64_t)F_ * 2, 128};
        cuuint32_t box3[3] = {64, 32, 2};
        enc(&hs.M.Wg3[o], BF, 3, (char*)wg + 64 * o, gd3, gs3, box3, es, IN, CU_TENSOR_MAP_SWIZZLE_128B, PR, OO);
        enc(&hs.M.Wu3[o], BF, 3, (char*)wu + 64 * o, gd3, gs3, box3, es, IN, CU_TENSOR_MAP_SWIZZLE_128B, PR, OO);
      }
    }
    {
      cuuint64_t gd[2] = {(cuuint64_t)D_, (cuuint64_t)F_}; cuuint64_t gs[1] = {(cuuint64_t)D_ * 2}; cuuint32_t box[2] = {64, 112};
      enc(&hs.M.Wd, BF, 2, wd, gd, gs, box, es, IN, CU_TENSOR_MAP_SWIZZLE_128B, PR, OO);
    }
    {
      void* pa = nullptr;
      cudaGetSymbolAddress(&pa, g_aT);
      cuuint64_t gd[2] = {(cuuint64_t)L_, (cuuint64_t)D_}; cuuint64_t gs[1] = {(cuuint64_t)L_ * 2}; cuuint32_t box[2] = {64, 64};
      enc(&hs.M.AT, BF, 2, pa, gd, gs, box, es, IN, CU_TENSOR_MAP_SWIZZLE_128B, PR, OO);
    }
    cudaFuncSetAttribute(fused_kernel, cudaFuncAttributeMaxDynamicSharedMemorySize, SM_TOTAL);
    hs.key[0] = x; hs.key[1] = wg; hs.key[2] = wu; hs.key[3] = wd;
    hs.ready = true;
  }
  Params P;
  P.x = (const __nv_bfloat16*)d_in[0];
  P.log_A_real = (const __nv_bfloat16*)d_in[1];
  P.A_imag = (const __nv_bfloat16*)d_in[2];
  P.C_real = (const __nv_bfloat16*)d_in[3];
  P.C_imag = (const __nv_bfloat16*)d_in[4];
  P.log_dt = (const __nv_bfloat16*)d_in[5];
  P.D_skip = (const __nv_bfloat16*)d_in[6];
  P.gate_w = (const __nv_bfloat16*)d_in[11];
  P.w_gate = (const __nv_bfloat16*)wg;
  P.w_up = (const __nv_bfloat16*)wu;
  P.w_down = (const __nv_bfloat16*)wd;
  P.out = (__nv_bfloat16*)d_out;
  fused_kernel<<<NCTA, NTHREADS, SM_TOTAL>>>(hs.M, P);
}
```

```cpp
#include <cuda_runtime.h>
#include <cuda_bf16.h>
#include <cuda.h>
#include <stdint.h>

#define PUBMODE 2
namespace {

constexpr int L_ = 2048, D_ = 512, F_ = 1792, NS_ = 128;
constexpr int NCTA = 128;
constexpr int NTHREADS = 384;

constexpr int SM_X = 0;
constexpr int SM_RING = 131072;
constexpr int KC_STRIDE = 656;
constexpr int SM_KB = 212992;
constexpr int SM_PR = SM_KB + 4 * KC_STRIDE * 2;
constexpr int SM_BAR = SM_PR + 512 * 24;
constexpr int SM_TOTAL = SM_BAR + 512;
constexpr int CV_R = 0;
constexpr int R_HALF = 156 * 16;
constexpr int R_CH = 2 * R_HALF;
constexpr int CV_E = 4 * R_CH;
constexpr int E_COPY = 4160;
constexpr int E_CH = 2 * E_COPY;
constexpr int CV_S = CV_E + 4 * E_CH;
constexpr int S_PITCH = 136;
constexpr int S_WG = 4 * 16 * S_PITCH * 4;
constexpr int SM_AT = SM_X;
static_assert(CV_S + 2 * S_WG <= 131072, "conv region");

constexpr int B_FULL = 0, B_EMPTY = 5, B_XFULL = 10, B_XFREE = 18, B_ATILE = 26, B_RRDY = 27, B_ADONE = 28, B_KPART = 29, B_KSUM = 30, B_SENT = 35, B_GOT = 43, B_STF = 51;

__device__ uint4 g_part[16 * 8 * 8 * 8 * 4 * 32];
__device__ uint32_t g_flag[16 * 8 * 8];
__device__ __align__(1024) __nv_bfloat16 g_aT[D_ * L_];
__device__ float g_gate[L_];
__device__ uint32_t g_done1;
__device__ uint32_t g_cnt[8 * 32];
__device__ uint32_t g_exit;
__device__ uint32_t g_zero;
__device__ uint32_t g_epoch;

#define TM_IF(cond, idx) do {} while (0)
#define FAIL(a, ph) break
#define SPIN_LIMIT (1 << 22)
#define MBAR_LIMIT (1 << 20)
__device__ __forceinline__ uint32_t smem_u32(const void* p) { return (uint32_t)__cvta_generic_to_shared(p); }
__device__ __forceinline__ void mbar_init(uint32_t a, uint32_t c) { asm volatile("mbarrier.init.shared::cta.b64 [%0], %1;" ::"r"(a), "r"(c) : "memory"); }
__device__ __forceinline__ void mbar_expect(uint32_t a, uint32_t bytes) { asm volatile("mbarrier.arrive.expect_tx.shared::cta.b64 _, [%0], %1;" ::"r"(a), "r"(bytes) : "memory"); }
__device__ __forceinline__ void mbar_arrive(uint32_t a) { asm volatile("mbarrier.arrive.shared::cta.b64 _, [%0];" ::"r"(a) : "memory"); }
__device__ __forceinline__ void mbar_wait(uint32_t a, uint32_t ph) {
  asm volatile("{\n.reg .pred p;\n.reg .u32 c;\nmov.u32 c, 0;\nLW:\nmbarrier.try_wait.parity.shared::cta.b64 p, [%0], %1, %2;\n@p bra LD;\n"
               "add.u32 c, c, 1;\nsetp.lt.u32 p, c, 1048576;\n@p bra LW;\nLD:\n}" ::"r"(a), "r"(ph), "r"(20000u) : "memory");
}
template <int NS> __device__ __forceinline__ void mbar_wait_lazy(uint32_t a, uint32_t ph) {
  asm volatile("{\n.reg .pred p;\n.reg .u32 c;\nmov.u32 c, 0;\nLW:\nmbarrier.test_wait.parity.shared::cta.b64 p, [%0], %1;\n@p bra LD;\n"
               "nanosleep.u32 %2;\nadd.u32 c, c, 1;\nsetp.lt.u32 p, c, 4194304;\n@p bra LW;\nLD:\n}" ::"r"(a), "r"(ph), "n"(NS) : "memory");
}
__device__ __forceinline__ void tma2d(uint32_t dst, const CUtensorMap* m, int c0, int c1, uint32_t bar) {
  asm volatile("cp.async.bulk.tensor.2d.shared::cluster.global.mbarrier::complete_tx::bytes [%0], [%1, {%3,%4}], [%2];" ::"r"(dst), "l"(m), "r"(bar), "r"(c0), "r"(c1) : "memory");
}
__device__ __forceinline__ void tma3d(uint32_t dst, const CUtensorMap* m, int c0, int c1, int c2, uint32_t bar) {
  asm volatile("cp.async.bulk.tensor.3d.shared::cluster.global.mbarrier::complete_tx::bytes [%0], [%1, {%3,%4,%5}], [%2];" ::"r"(dst), "l"(m), "r"(bar), "r"(c0), "r"(c1), "r"(c2) : "memory");
}
__device__ __forceinline__ uint64_t mkdesc(uint32_t addr, uint32_t lbo, uint32_t sbo, uint32_t sw) {
  return (uint64_t)((addr & 0x3FFFF) >> 4) | ((uint64_t)(lbo >> 4) << 16) | ((uint64_t)(sbo >> 4) << 32) | ((uint64_t)sw << 62);
}
__device__ __forceinline__ void wg_fence() { asm volatile("wgmma.fence.sync.aligned;" ::: "memory"); }
__device__ __forceinline__ void wg_commit() { asm volatile("wgmma.commit_group.sync.aligned;" ::: "memory"); }
template <int N> __device__ __forceinline__ void wg_wait() { asm volatile("wgmma.wait_group.sync.aligned %0;" ::"n"(N) : "memory"); }
__device__ __forceinline__ void zero_reg(float& x) { asm volatile("mov.f32 %0, 0f00000000;" : "=f"(x)); }
__device__ __forceinline__ void movf(float& d, float s) { asm volatile("mov.f32 %0, %1;" : "=f"(d) : "f"(s)); }
__device__ __forceinline__ void bar_sync(int id, int n) { asm volatile("bar.sync %0, %1;" ::"r"(id), "r"(n) : "memory"); }
__device__ __forceinline__ void fence_async() { asm volatile("fence.proxy.async.shared::cta;" ::: "memory"); }
__device__ __forceinline__ uint32_t pack_bf16(float lo, float hi) {
  uint32_t r;
  asm("cvt.rn.bf16x2.f32 %0, %1, %2;" : "=r"(r) : "f"(hi), "f"(lo));
  return r;
}
__device__ __forceinline__ uint32_t hmul2_bf16(uint32_t a, uint32_t b) {
  uint32_t r;
  asm("mul.rn.bf16x2 %0, %1, %2;" : "=r"(r) : "r"(a), "r"(b));
  return r;
}
__device__ __forceinline__ uint32_t hadd2_bf16(uint32_t a, uint32_t b) {
  uint32_t r;
  asm("add.rn.bf16x2 %0, %1, %2;" : "=r"(r) : "r"(a), "r"(b));
  return r;
}
__device__ __forceinline__ float bf_lo(uint32_t v) { return __uint_as_float(v << 16); }
__device__ __forceinline__ float bf_hi(uint32_t v) { return __uint_as_float(v & 0xFFFF0000u); }
__device__ __forceinline__ float bf16r(float x) { return __bfloat162float(__float2bfloat16_rn(x)); }
__device__ __forceinline__ float ldbf(const __nv_bfloat16* p) { return __bfloat162float(*p); }
__device__ __forceinline__ uint32_t ld_acquire(const uint32_t* p) {
  uint32_t v;
  asm volatile("ld.acquire.gpu.global.u32 %0, [%1];" : "=r"(v) : "l"(p) : "memory");
  return v;
}
__device__ __forceinline__ void st_release(uint32_t* p, uint32_t v) { asm volatile("st.release.gpu.global.u32 [%0], %1;" ::"l"(p), "r"(v) : "memory"); }
__device__ __forceinline__ uint4 ld_cg4(const uint4* p) {
  uint4 v;
  asm volatile("ld.global.cg.v4.u32 {%0,%1,%2,%3}, [%4];" : "=r"(v.x), "=r"(v.y), "=r"(v.z), "=r"(v.w) : "l"(p) : "memory");
  return v;
}
__device__ __forceinline__ uint32_t ld_cg1(const void* p) {
  uint32_t v;
  asm volatile("ld.global.cg.u32 %0, [%1];" : "=r"(v) : "l"(p) : "memory");
  return v;
}
__device__ __forceinline__ uint32_t lds32(uint32_t a) {
  uint32_t v;
  asm volatile("ld.shared.u32 %0, [%1];" : "=r"(v) : "r"(a) : "memory");
  return v;
}
__device__ __forceinline__ void ldsm4(uint32_t (&r)[4], uint32_t a) {
  asm volatile("ldmatrix.sync.aligned.m8n8.x4.shared.b16 {%0,%1,%2,%3}, [%4];" : "=r"(r[0]), "=r"(r[1]), "=r"(r[2]), "=r"(r[3]) : "r"(a) : "memory");
}
__device__ __forceinline__ uint32_t pack_f16(float lo, float hi) {
  uint32_t r;
  asm("cvt.rn.f16x2.f32 %0, %1, %2;" : "=r"(r) : "f"(hi), "f"(lo));
  return r;
}

__device__ __forceinline__ void wgmma_ss_n256(float (&d)[128], uint64_t da, uint64_t db) {
  asm volatile("wgmma.mma_async.sync.aligned.m64n256k16.f32.bf16.bf16 {%0, %1, %2, %3, %4, %5, %6, %7, %8, %9, %10, %11, %12, %13, %14, %15, %16, %17, %18, %19, %20, %21, %22, %23, %24, %25, %26, %27, %28, %29, %30, %31, %32, %33, %34, %35, %36, %37, %38, %39, %40, %41, %42, %43, %44, %45, %46, %47, %48, %49, %50, %51, %52, %53, %54, %55, %56, %57, %58, %59, %60, %61, %62, %63, %64, %65, %66, %67, %68, %69, %70, %71, %72, %73, %74, %75, %76, %77, %78, %79, %80, %81, %82, %83, %84, %85, %86, %87, %88, %89, %90, %91, %92, %93, %94, %95, %96, %97, %98, %99, %100, %101, %102, %103, %104, %105, %106, %107, %108, %109, %110, %111, %112, %113, %114, %115, %116, %117, %118, %119, %120, %121, %122, %123, %124, %125, %126, %127}, %128, %129, 1, 1, 1, 0, 1;"
    : "+f"(d[0]), "+f"(d[1]), "+f"(d[2]), "+f"(d[3]), "+f"(d[4]), "+f"(d[5]), "+f"(d[6]), "+f"(d[7]), "+f"(d[8]), "+f"(d[9]), "+f"(d[10]), "+f"(d[11]), "+f"(d[12]), "+f"(d[13]), "+f"(d[14]), "+f"(d[15]), "+f"(d[16]), "+f"(d[17]), "+f"(d[18]), "+f"(d[19]), "+f"(d[20]), "+f"(d[21]), "+f"(d[22]), "+f"(d[23]), "+f"(d[24]), "+f"(d[25]), "+f"(d[26]), "+f"(d[27]), "+f"(d[28]), "+f"(d[29]), "+f"(d[30]), "+f"(d[31]), "+f"(d[32]), "+f"(d[33]), "+f"(d[34]), "+f"(d[35]), "+f"(d[36]), "+f"(d[37]), "+f"(d[38]), "+f"(d[39]), "+f"(d[40]), "+f"(d[41]), "+f"(d[42]), "+f"(d[43]), "+f"(d[44]), "+f"(d[45]), "+f"(d[46]), "+f"(d[47]), "+f"(d[48]), "+f"(d[49]), "+f"(d[50]), "+f"(d[51]), "+f"(d[52]), "+f"(d[53]), "+f"(d[54]), "+f"(d[55]), "+f"(d[56]), "+f"(d[57]), "+f"(d[58]), "+f"(d[59]), "+f"(d[60]), "+f"(d[61]), "+f"(d[62]), "+f"(d[63]), "+f"(d[64]), "+f"(d[65]), "+f"(d[66]), "+f"(d[67]), "+f"(d[68]), "+f"(d[69]), "+f"(d[70]), "+f"(d[71]), "+f"(d[72]), "+f"(d[73]), "+f"(d[74]), "+f"(d[75]), "+f"(d[76]), "+f"(d[77]), "+f"(d[78]), "+f"(d[79]), "+f"(d[80]), "+f"(d[81]), "+f"(d[82]), "+f"(d[83]), "+f"(d[84]), "+f"(d[85]), "+f"(d[86]), "+f"(d[87]), "+f"(d[88]), "+f"(d[89]), "+f"(d[90]), "+f"(d[91]), "+f"(d[92]), "+f"(d[93]), "+f"(d[94]), "+f"(d[95]), "+f"(d[96]), "+f"(d[97]), "+f"(d[98]), "+f"(d[99]), "+f"(d[100]), "+f"(d[101]), "+f"(d[102]), "+f"(d[103]), "+f"(d[104]), "+f"(d[105]), "+f"(d[106]), "+f"(d[107]), "+f"(d[108]), "+f"(d[109]), "+f"(d[110]), "+f"(d[111]), "+f"(d[112]), "+f"(d[113]), "+f"(d[114]), "+f"(d[115]), "+f"(d[116]), "+f"(d[117]), "+f"(d[118]), "+f"(d[119]), "+f"(d[120]), "+f"(d[121]), "+f"(d[122]), "+f"(d[123]), "+f"(d[124]), "+f"(d[125]), "+f"(d[126]), "+f"(d[127]) : "l"(da), "l"(db));
}
__device__ __forceinline__ void wgmma_rs_n96(float (&d)[48], uint32_t a0, uint32_t a1, uint32_t a2, uint32_t a3, uint64_t db) {
  asm volatile("wgmma.mma_async.sync.aligned.m64n96k16.f32.bf16.bf16 {%0, %1, %2, %3, %4, %5, %6, %7, %8, %9, %10, %11, %12, %13, %14, %15, %16, %17, %18, %19, %20, %21, %22, %23, %24, %25, %26, %27, %28, %29, %30, %31, %32, %33, %34, %35, %36, %37, %38, %39, %40, %41, %42, %43, %44, %45, %46, %47}, {%48,%49,%50,%51}, %52, 1, 1, 1, 1;"
    : "+f"(d[0]), "+f"(d[1]), "+f"(d[2]), "+f"(d[3]), "+f"(d[4]), "+f"(d[5]), "+f"(d[6]), "+f"(d[7]), "+f"(d[8]), "+f"(d[9]), "+f"(d[10]), "+f"(d[11]), "+f"(d[12]), "+f"(d[13]), "+f"(d[14]), "+f"(d[15]), "+f"(d[16]), "+f"(d[17]), "+f"(d[18]), "+f"(d[19]), "+f"(d[20]), "+f"(d[21]), "+f"(d[22]), "+f"(d[23]), "+f"(d[24]), "+f"(d[25]), "+f"(d[26]), "+f"(d[27]), "+f"(d[28]), "+f"(d[29]), "+f"(d[30]), "+f"(d[31]), "+f"(d[32]), "+f"(d[33]), "+f"(d[34]), "+f"(d[35]), "+f"(d[36]), "+f"(d[37]), "+f"(d[38]), "+f"(d[39]), "+f"(d[40]), "+f"(d[41]), "+f"(d[42]), "+f"(d[43]), "+f"(d[44]), "+f"(d[45]), "+f"(d[46]), "+f"(d[47]) : "r"(a0), "r"(a1), "r"(a2), "r"(a3), "l"(db));
}
__device__ __forceinline__ void wgmma_rs_n64t(float (&d)[32], uint32_t a0, uint32_t a1, uint32_t a2, uint32_t a3, uint64_t db) {
  asm volatile("wgmma.mma_async.sync.aligned.m64n64k16.f32.bf16.bf16 {%0, %1, %2, %3, %4, %5, %6, %7, %8, %9, %10, %11, %12, %13, %14, %15, %16, %17, %18, %19, %20, %21, %22, %23, %24, %25, %26, %27, %28, %29, %30, %31}, {%32,%33,%34,%35}, %36, 1, 1, 1, 1;"
    : "+f"(d[0]), "+f"(d[1]), "+f"(d[2]), "+f"(d[3]), "+f"(d[4]), "+f"(d[5]), "+f"(d[6]), "+f"(d[7]), "+f"(d[8]), "+f"(d[9]), "+f"(d[10]), "+f"(d[11]), "+f"(d[12]), "+f"(d[13]), "+f"(d[14]), "+f"(d[15]), "+f"(d[16]), "+f"(d[17]), "+f"(d[18]), "+f"(d[19]), "+f"(d[20]), "+f"(d[21]), "+f"(d[22]), "+f"(d[23]), "+f"(d[24]), "+f"(d[25]), "+f"(d[26]), "+f"(d[27]), "+f"(d[28]), "+f"(d[29]), "+f"(d[30]), "+f"(d[31]) : "r"(a0), "r"(a1), "r"(a2), "r"(a3), "l"(db));
}
__device__ __forceinline__ void cw128z(float (&d)[64], uint32_t a0, uint32_t a1, uint32_t a2, uint32_t a3, uint64_t db) {
  asm volatile("{.reg .pred p; setp.ne.b32 p, 0, 0; wgmma.mma_async.sync.aligned.m64n128k16.f32.bf16.bf16 {%0, %1, %2, %3, %4, %5, %6, %7, %8, %9, %10, %11, %12, %13, %14, %15, %16, %17, %18, %19, %20, %21, %22, %23, %24, %25, %26, %27, %28, %29, %30, %31, %32, %33, %34, %35, %36, %37, %38, %39, %40, %41, %42, %43, %44, %45, %46, %47, %48, %49, %50, %51, %52, %53, %54, %55, %56, %57, %58, %59, %60, %61, %62, %63}, {%64,%65,%66,%67}, %68, p, 1, 1, 0;}"
    : "=f"(d[0]), "=f"(d[1]), "=f"(d[2]), "=f"(d[3]), "=f"(d[4]), "=f"(d[5]), "=f"(d[6]), "=f"(d[7]), "=f"(d[8]), "=f"(d[9]), "=f"(d[10]), "=f"(d[11]), "=f"(d[12]), "=f"(d[13]), "=f"(d[14]), "=f"(d[15]), "=f"(d[16]), "=f"(d[17]), "=f"(d[18]), "=f"(d[19]), "=f"(d[20]), "=f"(d[21]), "=f"(d[22]), "=f"(d[23]), "=f"(d[24]), "=f"(d[25]), "=f"(d[26]), "=f"(d[27]), "=f"(d[28]), "=f"(d[29]), "=f"(d[30]), "=f"(d[31]), "=f"(d[32]), "=f"(d[33]), "=f"(d[34]), "=f"(d[35]), "=f"(d[36]), "=f"(d[37]), "=f"(d[38]), "=f"(d[39]), "=f"(d[40]), "=f"(d[41]), "=f"(d[42]), "=f"(d[43]), "=f"(d[44]), "=f"(d[45]), "=f"(d[46]), "=f"(d[47]), "=f"(d[48]), "=f"(d[49]), "=f"(d[50]), "=f"(d[51]), "=f"(d[52]), "=f"(d[53]), "=f"(d[54]), "=f"(d[55]), "=f"(d[56]), "=f"(d[57]), "=f"(d[58]), "=f"(d[59]), "=f"(d[60]), "=f"(d[61]), "=f"(d[62]), "=f"(d[63]) : "r"(a0), "r"(a1), "r"(a2), "r"(a3), "l"(db));
}
__device__ __forceinline__ void cw128(float (&d)[64], uint32_t a0, uint32_t a1, uint32_t a2, uint32_t a3, uint64_t db) {
  asm volatile("wgmma.mma_async.sync.aligned.m64n128k16.f32.bf16.bf16 {%0, %1, %2, %3, %4, %5, %6, %7, %8, %9, %10, %11, %12, %13, %14, %15, %16, %17, %18, %19, %20, %21, %22, %23, %24, %25, %26, %27, %28, %29, %30, %31, %32, %33, %34, %35, %36, %37, %38, %39, %40, %41, %42, %43, %44, %45, %46, %47, %48, %49, %50, %51, %52, %53, %54, %55, %56, %57, %58, %59, %60, %61, %62, %63}, {%64,%65,%66,%67}, %68, 1, 1, 1, 0;"
    : "+f"(d[0]), "+f"(d[1]), "+f"(d[2]), "+f"(d[3]), "+f"(d[4]), "+f"(d[5]), "+f"(d[6]), "+f"(d[7]), "+f"(d[8]), "+f"(d[9]), "+f"(d[10]), "+f"(d[11]), "+f"(d[12]), "+f"(d[13]), "+f"(d[14]), "+f"(d[15]), "+f"(d[16]), "+f"(d[17]), "+f"(d[18]), "+f"(d[19]), "+f"(d[20]), "+f"(d[21]), "+f"(d[22]), "+f"(d[23]), "+f"(d[24]), "+f"(d[25]), "+f"(d[26]), "+f"(d[27]), "+f"(d[28]), "+f"(d[29]), "+f"(d[30]), "+f"(d[31]), "+f"(d[32]), "+f"(d[33]), "+f"(d[34]), "+f"(d[35]), "+f"(d[36]), "+f"(d[37]), "+f"(d[38]), "+f"(d[39]), "+f"(d[40]), "+f"(d[41]), "+f"(d[42]), "+f"(d[43]), "+f"(d[44]), "+f"(d[45]), "+f"(d[46]), "+f"(d[47]), "+f"(d[48]), "+f"(d[49]), "+f"(d[50]), "+f"(d[51]), "+f"(d[52]), "+f"(d[53]), "+f"(d[54]), "+f"(d[55]), "+f"(d[56]), "+f"(d[57]), "+f"(d[58]), "+f"(d[59]), "+f"(d[60]), "+f"(d[61]), "+f"(d[62]), "+f"(d[63]) : "r"(a0), "r"(a1), "r"(a2), "r"(a3), "l"(db));
}
__device__ __forceinline__ void cw96(float (&d)[48], uint32_t a0, uint32_t a1, uint32_t a2, uint32_t a3, uint64_t db) {
  asm volatile("wgmma.mma_async.sync.aligned.m64n96k16.f32.bf16.bf16 {%0, %1, %2, %3, %4, %5, %6, %7, %8, %9, %10, %11, %12, %13, %14, %15, %16, %17, %18, %19, %20, %21, %22, %23, %24, %25, %26, %27, %28, %29, %30, %31, %32, %33, %34, %35, %36, %37, %38, %39, %40, %41, %42, %43, %44, %45, %46, %47}, {%48,%49,%50,%51}, %52, 1, 1, 1, 0;"
    : "+f"(d[0]), "+f"(d[1]), "+f"(d[2]), "+f"(d[3]), "+f"(d[4]), "+f"(d[5]), "+f"(d[6]), "+f"(d[7]), "+f"(d[8]), "+f"(d[9]), "+f"(d[10]), "+f"(d[11]), "+f"(d[12]), "+f"(d[13]), "+f"(d[14]), "+f"(d[15]), "+f"(d[16]), "+f"(d[17]), "+f"(d[18]), "+f"(d[19]), "+f"(d[20]), "+f"(d[21]), "+f"(d[22]), "+f"(d[23]), "+f"(d[24]), "+f"(d[25]), "+f"(d[26]), "+f"(d[27]), "+f"(d[28]), "+f"(d[29]), "+f"(d[30]), "+f"(d[31]), "+f"(d[32]), "+f"(d[33]), "+f"(d[34]), "+f"(d[35]), "+f"(d[36]), "+f"(d[37]), "+f"(d[38]), "+f"(d[39]), "+f"(d[40]), "+f"(d[41]), "+f"(d[42]), "+f"(d[43]), "+f"(d[44]), "+f"(d[45]), "+f"(d[46]), "+f"(d[47]) : "r"(a0), "r"(a1), "r"(a2), "r"(a3), "l"(db));
}
__device__ __forceinline__ void cw64(float (&d)[32], uint32_t a0, uint32_t a1, uint32_t a2, uint32_t a3, uint64_t db) {
  asm volatile("wgmma.mma_async.sync.aligned.m64n64k16.f32.bf16.bf16 {%0, %1, %2, %3, %4, %5, %6, %7, %8, %9, %10, %11, %12, %13, %14, %15, %16, %17, %18, %19, %20, %21, %22, %23, %24, %25, %26, %27, %28, %29, %30, %31}, {%32,%33,%34,%35}, %36, 1, 1, 1, 0;"
    : "+f"(d[0]), "+f"(d[1]), "+f"(d[2]), "+f"(d[3]), "+f"(d[4]), "+f"(d[5]), "+f"(d[6]), "+f"(d[7]), "+f"(d[8]), "+f"(d[9]), "+f"(d[10]), "+f"(d[11]), "+f"(d[12]), "+f"(d[13]), "+f"(d[14]), "+f"(d[15]), "+f"(d[16]), "+f"(d[17]), "+f"(d[18]), "+f"(d[19]), "+f"(d[20]), "+f"(d[21]), "+f"(d[22]), "+f"(d[23]), "+f"(d[24]), "+f"(d[25]), "+f"(d[26]), "+f"(d[27]), "+f"(d[28]), "+f"(d[29]), "+f"(d[30]), "+f"(d[31]) : "r"(a0), "r"(a1), "r"(a2), "r"(a3), "l"(db));
}
__device__ __forceinline__ void cw32(float (&d)[16], uint32_t a0, uint32_t a1, uint32_t a2, uint32_t a3, uint64_t db) {
  asm volatile("wgmma.mma_async.sync.aligned.m64n32k16.f32.bf16.bf16 {%0, %1, %2, %3, %4, %5, %6, %7, %8, %9, %10, %11, %12, %13, %14, %15}, {%16,%17,%18,%19}, %20, 1, 1, 1, 0;"
    : "+f"(d[0]), "+f"(d[1]), "+f"(d[2]), "+f"(d[3]), "+f"(d[4]), "+f"(d[5]), "+f"(d[6]), "+f"(d[7]), "+f"(d[8]), "+f"(d[9]), "+f"(d[10]), "+f"(d[11]), "+f"(d[12]), "+f"(d[13]), "+f"(d[14]), "+f"(d[15]) : "r"(a0), "r"(a1), "r"(a2), "r"(a3), "l"(db));
}

struct cpx { float r, i; };
__device__ __forceinline__ cpx cmul(cpx a, cpx b) { return {fmaf(a.r, b.r, -a.i * b.i), fmaf(a.r, b.i, a.i * b.r)}; }
__device__ __forceinline__ cpx csqr(cpx a) { return {fmaf(a.r, a.r, -a.i * a.i), (a.r * a.i) * 2.f}; }
__device__ __forceinline__ cpx cmulc(cpx a, cpx b) { return {fmaf(a.r, b.r, -a.i * b.i), fmaf(-a.r, b.i, -a.i * b.r)}; }
__device__ __forceinline__ cpx cexp_fast(float re, float im) {
  float e;
  asm("ex2.approx.ftz.f32 %0, %1;" : "=f"(e) : "f"(re * 1.4426950408889634f));
  float k = rintf(im * 0.15915494309189535f);
  float r = fmaf(k, -6.2831854820251465f, im);
  r = fmaf(k, 1.7484555314695172e-07f, r);
  float s, c;
  asm("sin.approx.f32 %0, %1;" : "=f"(s) : "f"(r));
  asm("cos.approx.f32 %0, %1;" : "=f"(c) : "f"(r));
  return {e * c, e * s};
}

struct KOps { uint32_t xa[5], xb[5], y[4]; };
__device__ __forceinline__ void kgen_ops(KOps& o, const float4 pr, const float2 qq, const float gf) {
  const cpx C = {pr.z, pr.w};
  const cpx Q = {qq.x, qq.y};
  const cpx V0 = cexp_fast(pr.x * gf, pr.y * gf);
  const cpx V1 = csqr(V0), V2 = csqr(V1), V3 = csqr(V2);
  const cpx Y0 = cmulc(C, V0), Y1 = cmulc(C, V1), Y2 = cmulc(C, V2), Y3 = cmulc(C, V3);
  o.y[0] = pack_f16(Y0.r, Y0.i); o.y[1] = pack_f16(Y1.r, Y1.i); o.y[2] = pack_f16(Y2.r, Y2.i); o.y[3] = pack_f16(Y3.r, Y3.i);
  const cpx Xb = cmul(V3, Q);
  cpx Xc = cmul(Xb, Q), Xd = cmul(Xc, Q);
  o.xa[0] = pack_f16(V3.r, V3.i); o.xb[0] = pack_f16(Xb.r, Xb.i);
  o.xa[1] = pack_f16(Xc.r, Xc.i); o.xb[1] = pack_f16(Xd.r, Xd.i);
#pragma unroll
  for (int k = 2; k < 5; k++) {
    Xc = csqr(Xc); Xd = csqr(Xd);
    o.xa[k] = pack_f16(Xc.r, Xc.i); o.xb[k] = pack_f16(Xd.r, Xd.i);
  }
}
__device__ __forceinline__ void kgen_mma(float (&T)[5][4], const KOps& a, const KOps& b) {
  asm("mma.sync.aligned.m16n8k16.row.col.f32.f16.f16.f32 {%0,%1,%2,%3}, {%20,%21,%22,%23}, {%40,%41}, {%0,%1,%2,%3};\n"
      "mma.sync.aligned.m16n8k16.row.col.f32.f16.f16.f32 {%4,%5,%6,%7}, {%24,%25,%26,%27}, {%40,%41}, {%4,%5,%6,%7};\n"
      "mma.sync.aligned.m16n8k16.row.col.f32.f16.f16.f32 {%8,%9,%10,%11}, {%28,%29,%30,%31}, {%42,%43}, {%8,%9,%10,%11};\n"
      "mma.sync.aligned.m16n8k16.row.col.f32.f16.f16.f32 {%12,%13,%14,%15}, {%32,%33,%34,%35}, {%44,%45}, {%12,%13,%14,%15};\n"
      "mma.sync.aligned.m16n8k16.row.col.f32.f16.f16.f32 {%16,%17,%18,%19}, {%36,%37,%38,%39}, {%46,%47}, {%16,%17,%18,%19};\n"
      : "+f"(T[0][0]), "+f"(T[0][1]), "+f"(T[0][2]), "+f"(T[0][3]), "+f"(T[1][0]), "+f"(T[1][1]), "+f"(T[1][2]), "+f"(T[1][3]),
        "+f"(T[2][0]), "+f"(T[2][1]), "+f"(T[2][2]), "+f"(T[2][3]), "+f"(T[3][0]), "+f"(T[3][1]), "+f"(T[3][2]), "+f"(T[3][3]),
        "+f"(T[4][0]), "+f"(T[4][1]), "+f"(T[4][2]), "+f"(T[4][3])
      : "r"(a.xa[0]), "r"(a.xb[0]), "r"(b.xa[0]), "r"(b.xb[0]), "r"(a.xa[1]), "r"(a.xb[1]), "r"(b.xa[1]), "r"(b.xb[1]),
        "r"(a.xa[2]), "r"(a.xb[2]), "r"(b.xa[2]), "r"(b.xb[2]), "r"(a.xa[3]), "r"(a.xb[3]), "r"(b.xa[3]), "r"(b.xb[3]),
        "r"(a.xa[4]), "r"(a.xb[4]), "r"(b.xa[4]), "r"(b.xb[4]),
        "r"(a.y[0]), "r"(b.y[0]), "r"(a.y[1]), "r"(b.y[1]), "r"(a.y[2]), "r"(b.y[2]), "r"(a.y[3]), "r"(b.y[3]));
}

template <int J0> __device__ __forceinline__ void conv_load4(uint32_t (&f)[4][4], uint32_t ebase, uint32_t zero) {
#pragma unroll
  for (int t = 0; t < 4; t++) {
    f[t][0] = lds32(ebase + (J0 + t) * 128);
    f[t][1] = lds32(ebase + (J0 + t) * 128 + 16);
    f[t][3] = lds32(ebase + (J0 + t) * 128 + 32);
  }
#pragma unroll
  for (int t = 0; t < 4; t++) f[t][2] = f[t][1] ^ zero;
}
#define CONV_GRP(FN, ACC, J0, F)                                                             \
  wg_fence();                                                                                \
  FN(ACC, F[0][0], F[0][1], F[0][2], F[0][3], de + 4 * (J0));                                \
  FN(ACC, F[1][0], F[1][1], F[1][2], F[1][3], de + 4 * (J0 + 1));                            \
  FN(ACC, F[2][0], F[2][1], F[2][2], F[2][3], de + 4 * (J0 + 2));                            \
  FN(ACC, F[3][0], F[3][1], F[3][2], F[3][3], de + 4 * (J0 + 3));                            \
  wg_commit();
#define CONV_STAGE(ACC, M0)                                                                  \
  _Pragma("unroll") for (int m = (M0); m < (M0) + 4; m++) {                                  \
    *(float2*)(Sw + 8 * m) = make_float2(ACC[4 * m], ACC[4 * m + 1]);                        \
    *(float2*)(Sw + 8 * S_PITCH + 8 * m) = make_float2(ACC[4 * m + 2], ACC[4 * m + 3]);      \
  }
#define CONV_CHANNEL(PRE, MID1, MID2)                                                                    \
  {                                                                                          \
    float a128[64], a96[48], a64[32], a32[16];                                               \
    wg_fence();                                                                              \
    cw128z(a128, fa[0][0], fa[0][1], fa[0][2], fa[0][3], de);                                \
    cw128(a128, fa[1][0], fa[1][1], fa[1][2], fa[1][3], de + 4);                             \
    cw128(a128, fa[2][0], fa[2][1], fa[2][2], fa[2][3], de + 8);                             \
    cw128(a128, fa[3][0], fa[3][1], fa[3][2], fa[3][3], de + 12);                            \
    wg_commit();                                                                             \
    CONV_GRP(cw128, a128, 4, fb)                                                             \
    MID1                                                                                     \
    wg_wait<1>(); conv_load4<8>(fa, ebase, zero);                                            \
    wg_wait<0>(); conv_load4<12>(fb, ebase, zero);                                           \
    _Pragma("unroll") for (int i = 0; i < 48; i++) movf(a96[i], a128[i]);                       \
    CONV_GRP(cw96, a96, 8, fa)                                                               \
    CONV_GRP(cw96, a96, 12, fb)                                                              \
    MID2                                                                                     \
    PRE                                                                                      \
    CONV_STAGE(a128, 12)                                                                     \
    wg_wait<1>(); conv_load4<16>(fa, ebase, zero);                                           \
    wg_wait<0>(); conv_load4<20>(fb, ebase, zero);                                           \
    _Pragma("unroll") for (int i = 0; i < 32; i++) movf(a64[i], a96[i]);                        \
    CONV_GRP(cw64, a64, 16, fa)                                                              \
    CONV_GRP(cw64, a64, 20, fb)                                                              \
    CONV_STAGE(a96, 8)                                                                       \
    wg_wait<1>(); conv_load4<24>(fa, ebase, zero);                                           \
    wg_wait<0>(); conv_load4<28>(fb, ebase, zero);                                           \
    _Pragma("unroll") for (int i = 0; i < 16; i++) movf(a32[i], a64[i]);                        \
    CONV_GRP(cw32, a32, 24, fa)                                                              \
    CONV_GRP(cw32, a32, 28, fb)                                                              \
    CONV_STAGE(a64, 4)                                                                       \
    load_u(ch);                                                                              \
    wg_wait<0>();                                                                            \
    CONV_STAGE(a32, 0)                                                                       \
  }

template <int V> struct IC { static constexpr int value = V; };

struct Params {
  const __nv_bfloat16* x;
  const __nv_bfloat16* log_A_real;
  const __nv_bfloat16* A_imag;
  const __nv_bfloat16* C_real;
  const __nv_bfloat16* C_imag;
  const __nv_bfloat16* log_dt;
  const __nv_bfloat16* D_skip;
  const __nv_bfloat16* gate_w;
  const __nv_bfloat16* w_gate;
  const __nv_bfloat16* w_up;
  const __nv_bfloat16* w_down;
  __nv_bfloat16* out;
};

struct Maps {
  CUtensorMap X, Wg, Wu, Wg3[2], Wu3[2], Wd, AT;
};

__device__ __forceinline__ uint32_t ld_epoch() { return *(volatile uint32_t*)&g_epoch; }
__device__ __forceinline__ uint32_t dup_lo(uint32_t w) { return __byte_perm(w, w, 0x1010); }
__device__ __forceinline__ uint32_t dup_hi(uint32_t w) { return __byte_perm(w, w, 0x3232); }

__global__ void __launch_bounds__(NTHREADS, 1)
fused_kernel(const __grid_constant__ Maps M, const Params P) {
  extern __shared__ __align__(1024) uint8_t smem[];
  const uint32_t sb = smem_u32(smem);
  const uint32_t bars = sb + SM_BAR;
  const int tid = threadIdx.x;
  const int warp = __shfl_sync(0xffffffffu, tid >> 5, 0), lane = tid & 31;
  const int b = blockIdx.x;
  const int cl = b >> 1;
  const int jf = cl & 7;
  const int it_ = ((cl >> 3) << 1) | (b & 1);
  const int d0 = b * 4;

  const int kch = warp / 3, kpart = warp - 3 * kch;
  const int kk0 = kpart == 0 ? 0 : (kpart == 1 ? 6 : 11), nks = kpart == 0 ? 6 : 5;
  uint32_t pw0[2], pw1[2], pldt;
#pragma unroll
  for (int r = 0; r < 2; r++) {
    int n = 8 * kk0 + lane + 32 * r;
    n = (d0 + kch) * NS_ + (n < NS_ ? n : NS_ - 1);
    pw0[r] = (uint32_t)*(const unsigned short*)(P.log_A_real + n) | ((uint32_t)*(const unsigned short*)(P.A_imag + n) << 16);
    pw1[r] = (uint32_t)*(const unsigned short*)(P.C_real + n) | ((uint32_t)*(const unsigned short*)(P.C_imag + n) << 16);
  }
  pldt = *(const unsigned short*)(P.log_dt + d0 + kch);
  if (lane == 0) {
#pragma unroll
    for (int r = 0; r < 5; r++) {
      const int i = warp + 12 * r;
      uint32_t cnt = 1;
      if ((i >= B_EMPTY && i < B_EMPTY + 5) || (i >= B_XFREE && i < B_XFREE + 8) || (i >= B_SENT && i < B_SENT + 8) || i == B_ADONE) cnt = 8;
      if (i == B_RRDY || i == B_KSUM) cnt = 2;
      if (i == B_KPART) cnt = 12;
      if (i == B_GOT) cnt = 7;
      mbar_init(bars + 8 * i, cnt);
    }
    asm volatile("fence.mbarrier_init.release.cluster;" ::: "memory");
  }
  TM_IF(tid == 0, 20);
  __syncthreads();
  TM_IF(tid == 0, 21);

  auto issue_stage = [&](int s, int slot) {
    const uint32_t dst = sb + SM_RING + slot * 16384;
    const uint32_t fb = bars + 8 * (B_FULL + slot);
    if (s < 32) {
      const int f0 = jf * 224 + ((s >> 4) << 7);
      const int k0 = (s & 15) * 32;
      mbar_expect(fb, 16384);
      if (jf == 7 && s >= 16) {
        tma2d(dst, &M.Wg, f0, k0, fb);
        tma2d(dst + 4096, &M.Wg, f0 + 64, k0, fb);
        tma2d(dst + 8192, &M.Wu, f0, k0, fb);
        tma2d(dst + 12288, &M.Wu, f0 + 64, k0, fb);
      } else {
        tma3d(dst, &M.Wg3[jf & 1], 0, k0, f0 >> 6, fb);
        tma3d(dst + 8192, &M.Wu3[jf & 1], 0, k0, f0 >> 6, fb);
      }
    } else {
      const int s2 = s - 32;
      const int p = (jf + 1 + (s2 >> 1)) & 7;
      mbar_expect(fb, 14336);
      tma2d(dst, &M.Wd, p * 64, jf * 224 + (s2 & 1) * 112, fb);
    }
  };
  auto issue_x = [&](int kb) {
    mbar_expect(bars + 8 * (B_XFULL + kb), 16384);
    tma2d(sb + SM_X + kb * 16384, &M.X, kb * 64, it_ * 128, bars + 8 * (B_XFULL + kb));
  };
  {
    const int g = lane >> 2, q = lane & 3;
    const float dtf = bf16r(expf(bf_lo(pldt)));
    const int pro = kch * 128 + 8 * kk0;
    float4* prm = (float4*)(smem + SM_PR) + pro;
    float2* prq = (float2*)(smem + SM_PR + 512 * 16) + pro;
    const bool valid1 = lane + 32 < 8 * nks;
    float m0 = fmaxf(fmaxf(fabsf(bf_lo(pw1[0])), fabsf(bf_hi(pw1[0]))), fmaxf(fabsf(bf_lo(pw1[1])), fabsf(bf_hi(pw1[1])))) * dtf;
#pragma unroll
    for (int o = 16; o > 0; o >>= 1) m0 = fmaxf(m0, __shfl_xor_sync(0xffffffffu, m0, o));
    TM_IF(tid == 0 && m0 >= 0.f, 0);
    if (m0 >= 0.f || m0 != m0) {
      if (tid == 256) {
        issue_x(0); issue_stage(0, 0); issue_stage(2, 2); issue_x(2); issue_stage(4, 4); issue_x(4);
      } else if (tid == 288) {
        issue_stage(1, 1); issue_x(1); issue_stage(3, 3); issue_x(3); issue_x(5);
      }
    }
    __syncwarp();
    const uint32_t e0 = min(max(__float_as_uint(m0) >> 23, 1u), 253u);
    const float sc = __uint_as_float((254u - e0) << 23);
    const float us = 2.f * __uint_as_float(e0 << 23);
    float pe = 0.f;
#pragma unroll
    for (int r = 0; r < 2; r++) {
      float4 v;
      v.x = -bf16r(expf(bf_lo(pw0[r]))) * dtf;
      v.y = bf_hi(pw0[r]) * dtf;
      v.z = bf_lo(pw1[r]) * dtf * sc;
      v.w = bf_hi(pw1[r]) * dtf * sc;
      const cpx Q = cexp_fast(v.x * 64.f, v.y * 64.f);
      const cpx We = cexp_fast(v.x * 2048.f, v.y * 2048.f);
      if (r == 0 || valid1) {
        pe += v.z * We.r - v.w * We.i;
        prm[lane + 32 * r] = v;
        prq[lane + 32 * r] = make_float2(Q.r, Q.i);
      }
    }
#pragma unroll
    for (int o = 16; o > 0; o >>= 1) pe += __shfl_xor_sync(0xffffffffu, pe, o);
    __syncwarp();
    TM_IF(tid == 0, 1);
    float T[5][4];
#pragma unroll
    for (int i = 0; i < 20; i++) T[i >> 2][i & 3] = 0.f;
    const float gf = (float)g;
#pragma unroll 1
    for (int ks = 0; ks < nks; ks++) {
      KOps o1, o2;
      kgen_ops(o1, prm[8 * ks + q], prq[8 * ks + q], gf);
      kgen_ops(o2, prm[8 * ks + 4 + q], prq[8 * ks + 4 + q], gf);
      kgen_mma(T, o1, o2);
    }
    float* kp = (float*)(smem + SM_X + 6 * 16384) + warp * KC_STRIDE + 8 * g + 2 * q;
#pragma unroll
    for (int k = 0; k < 5; k++) {
      *(float2*)(kp + 128 * k) = make_float2(T[k][0] * us, T[k][1] * us);
      *(float2*)(kp + 128 * k + 64) = make_float2(T[k][2] * us, T[k][3] * us);
    }
    if (lane == 0) { kp[640] = pe * us; kp[641] = 0.f; }
    TM_IF(tid == 0, 2);
    __syncwarp();
    if (lane == 0) mbar_arrive(bars + 8 * B_KPART);
  }

  if (warp >= 8) {
    asm volatile("setmaxnreg.dec.sync.aligned.u32 104;");
    if (warp < 10) {
      if (lane == 0) {
        int slot = (warp == 8) ? 1 : 0;
        uint32_t ph = 0;
#pragma unroll 1
        for (int s = (warp == 8) ? 6 : 5; s < 48; s += 2) {
          if (s == 10) { mbar_wait(bars + 8 * B_KSUM, 0); issue_x(6); issue_x(7); }
          mbar_wait(bars + 8 * (B_EMPTY + slot), ph);
          issue_stage(s, slot);
          slot += 2;
          if (slot >= 5) { slot -= 5; ph ^= 1; }
        }
      }
      __syncwarp();
      {
        const uint4 gw0 = *(const uint4*)(P.gate_w + lane * 16);
        const uint4 gw1 = *(const uint4*)(P.gate_w + lane * 16 + 8);
        uint4 xa[8], xb[8];
#pragma unroll
        for (int i = 0; i < 8; i++) {
          xa[i] = *(const uint4*)(P.x + (b * 16 + (warp - 8) * 8 + i) * D_ + lane * 16);
          xb[i] = *(const uint4*)(P.x + (b * 16 + (warp - 8) * 8 + i) * D_ + lane * 16 + 8);
        }
        float sg[8];
#pragma unroll
        for (int i = 0; i < 8; i++) {
          const uint32_t pr[8] = {hmul2_bf16(xa[i].x, gw0.x), hmul2_bf16(xa[i].y, gw0.y), hmul2_bf16(xa[i].z, gw0.z), hmul2_bf16(xa[i].w, gw0.w),
                                  hmul2_bf16(xb[i].x, gw1.x), hmul2_bf16(xb[i].y, gw1.y), hmul2_bf16(xb[i].z, gw1.z), hmul2_bf16(xb[i].w, gw1.w)};
          float s = 0.f;
#pragma unroll
          for (int k = 0; k < 8; k++) s += bf_lo(pr[k]) + bf_hi(pr[k]);
          sg[i] = s;
        }
#pragma unroll
        for (int o = 16; o > 0; o >>= 1) {
#pragma unroll
          for (int i = 0; i < 8; i++) sg[i] += __shfl_xor_sync(0xffffffffu, sg[i], o);
        }
        float z = sg[0];
#pragma unroll
        for (int i = 1; i < 8; i++) z = (lane == i) ? sg[i] : z;
        if (lane < 8) g_gate[b * 16 + (warp - 8) * 8 + lane] = bf16r(1.f / (1.f + expf(-bf16r(z))));
      }
      bar_sync(3, 64);
      if (tid == 288) asm volatile("red.release.gpu.global.add.u32 [%0], 1;" ::"l"(&g_done1) : "memory");
      TM_IF(tid == 256, 16);
      if (warp == 8) {
        if (lane >= 1 && lane < 8) {
          const uint32_t tag = ld_epoch() + 1;
          const uint32_t* fp = g_flag + ((it_ * 8 + jf) * 8 + ((jf - lane) & 7));
          int itc = 0;
          while (ld_acquire(fp) != tag) { __nanosleep(100); if (++itc > SPIN_LIMIT) FAIL(-2, lane); }
          mbar_arrive(bars + 8 * B_GOT);
          TM_IF(lane == 7, 25);
        }
      } else if (lane == 0) {
        const uint32_t tag = ld_epoch() + 1;
#pragma unroll 1
        for (int rnd = 0; rnd < 2; rnd++) {
          if (rnd == 1) {
            int itc = 0;
            while ((int)(ld_acquire(&g_done1) - (uint32_t)NCTA * tag) < 0) { if (++itc > SPIN_LIMIT) FAIL(-1, 0); }
            mbar_wait(bars + 8 * B_ADONE, 1);
          } else {
            mbar_wait_lazy<100>(bars + 8 * B_ADONE, 0);
          }
          TM_IF(true, 24);
#pragma unroll
          for (int v = 0; v < 2; v++)
            asm volatile("cp.async.bulk.global.shared::cta.bulk_group [%0], [%1], %2;"
                         ::"l"(g_aT + (d0 + 2 * v + rnd) * L_), "r"(sb + SM_X + CV_R + (2 * v + rnd) * R_CH), "r"(4096) : "memory");
          asm volatile("cp.async.bulk.commit_group;" ::: "memory");
          asm volatile("cp.async.bulk.wait_group 0;" ::: "memory");
          asm volatile("red.relaxed.gpu.global.add.u32 [%0], 1;" ::"l"(g_cnt + 32 * (b >> 4)) : "memory");
        }
        TM_IF(true, 26);
        {
          int itc = 0;
          while ((int)(ld_acquire(g_cnt + 32 * jf) - 32u * tag) < 0) { if (++itc > SPIN_LIMIT) FAIL(-3, 0); }
        }
        TM_IF(true, 23);
        asm volatile("fence.proxy.async.global;" ::: "memory");
        mbar_expect(bars + 8 * B_ATILE, 16384);
        tma2d(sb + SM_AT, &M.AT, it_ * 128, jf * 64, bars + 8 * B_ATILE);
        tma2d(sb + SM_AT + 8192, &M.AT, it_ * 128 + 64, jf * 64, bars + 8 * B_ATILE);
      }
      __syncwarp();
    } else {
      const int w = warp - 10;
      const int wt = tid - 320;
      mbar_wait(bars + 8 * B_KPART, 0);
      {
        const float2* kp = (const float2*)(smem + SM_X + 6 * 16384);
        uint32_t* kb = (uint32_t*)(smem + SM_KB);
#pragma unroll
        for (int ch = 0; ch < 4; ch++) {
#pragma unroll
          for (int i = 0; i < 6; i++) {
            const int o = wt + 64 * i;
            if (i < 5 || o < 321) {
              const float2 a0 = kp[(3 * ch) * (KC_STRIDE / 2) + o], a1 = kp[(3 * ch + 1) * (KC_STRIDE / 2) + o], a2 = kp[(3 * ch + 2) * (KC_STRIDE / 2) + o];
              kb[ch * (KC_STRIDE / 2) + o] = pack_bf16(a0.x + a1.x + a2.x, a0.y + a1.y + a2.y);
            }
          }
        }
      }
      fence_async();
      bar_sync(1, 64);
      if (lane == 0) mbar_arrive(bars + 8 * B_KSUM);
      {
        const uint32_t zz = *(volatile uint32_t*)&g_zero;
        uint2 ur[4][8];
#pragma unroll
        for (int i = 0; i < 4; i++) {
#pragma unroll
          for (int r = 0; r < 8; r++) {
            uint32_t ck;
            asm volatile("nanosleep.u32 120;\n\tmov.u32 %0, %%clock;" : "=r"(ck) :: "memory");
            asm volatile("ld.global.nc.v2.u32 {%0,%1}, [%2];" : "=r"(ur[i][r].x), "=r"(ur[i][r].y)
                         : "l"(P.x + ((wt + 64 * i) * 8 + r) * D_ + d0 + (ck & zz)));
          }
        }
        mbar_wait_lazy<200>(bars + 8 * (B_XFREE + 7), 0);
        TM_IF(wt == 0, 18);
#pragma unroll
        for (int i = 0; i < 4; i++) {
          const int item = wt + 64 * i;
          const int c = item >> 1, hh = item & 1;
#pragma unroll
          for (int ch = 0; ch < 4; ch++) {
            uint32_t v[4];
#pragma unroll
            for (int k = 0; k < 4; k++) {
              const uint32_t lo = (ch < 2) ? ur[i][7 - 2 * k].x : ur[i][7 - 2 * k].y;
              const uint32_t hi = (ch < 2) ? ur[i][6 - 2 * k].x : ur[i][6 - 2 * k].y;
              v[k] = (ch & 1) ? __byte_perm(lo, hi, 0x7632) : __byte_perm(lo, hi, 0x5410);
            }
            *(uint4*)(smem + SM_X + CV_R + ch * R_CH + (1 - hh) * R_HALF + (127 - c) * 16) = make_uint4(v[0], v[1], v[2], v[3]);
          }
        }
        if (lane < 28) {
#pragma unroll
          for (int z = 0; z < 4; z++)
            *(uint4*)(smem + SM_X + CV_R + (4 * w + z) * R_HALF + (128 + lane) * 16) = make_uint4(0, 0, 0, 0);
        }
      }
      auto part_store = [&](int s) {
        mbar_wait_lazy<100>(bars + 8 * (B_SENT + s), 0);
        const int fi = (it_ * 8 + ((jf + 1 + s) & 7)) * 8 + jf;
#pragma unroll
        for (int v = 0; v < 2; v++)
          asm volatile("cp.async.bulk.global.shared::cta.bulk_group [%0], [%1], %2;"
                       ::"l"(g_part + (size_t)fi * 1024 + v * 512), "r"(sb + SM_X + (s == 6 ? CV_E + 2 * v * E_CH : CV_S + v * S_WG + (s & 3) * 8192)), "r"(8192) : "memory");
        asm volatile("cp.async.bulk.commit_group;" ::: "memory");
      };
      if (w == 0 && lane == 0) part_store(0);
      __syncwarp();
      {
#pragma unroll 1
      for (int G = w; G < 8; G += 2) {
        const int n = 32 * G + lane;
        uint4 c0[4], c1[4];
        if (G >= 4) {
#pragma unroll
          for (int ch = 0; ch < 4; ch++) {
            const uint8_t* kc = smem + SM_KB + ch * KC_STRIDE * 2;
            const uint32_t a = *(const unsigned short*)(kc + (384 + n) * 2), bb = *(const unsigned short*)(kc + (385 + n) * 2);
            const uint32_t aa = a | (a << 16), b2 = bb | (bb << 16);
            const uint32_t tie = (n & 1) ? bb : a;
            c0[ch] = make_uint4(aa, a | (tie << 16), b2, b2);
            c1[ch] = make_uint4(aa, tie | (bb << 16), b2, b2);
          }
        } else if (G >= 2) {
#pragma unroll
          for (int ch = 0; ch < 4; ch++) {
            const uint8_t* kc = smem + SM_KB + ch * KC_STRIDE * 2;
            const uint32_t w0 = *(const uint32_t*)(kc + (256 + 2 * n) * 2), w1 = *(const uint32_t*)(kc + (258 + 2 * n) * 2);
            c0[ch] = make_uint4(dup_lo(w0), dup_hi(w0), __byte_perm(w0, w1, 0x5432), dup_lo(w1));
            c1[ch] = make_uint4(w0, dup_hi(w0), dup_lo(w1), dup_lo(w1));
          }
        } else if (G == 1) {
#pragma unroll
          for (int ch = 0; ch < 4; ch++) {
            const uint8_t* kc = smem + SM_KB + ch * KC_STRIDE * 2;
            const uint2 w01 = *(const uint2*)(kc + (128 + 4 * n) * 2);
            const uint32_t w2 = *(const uint32_t*)(kc + (132 + 4 * n) * 2);
            c0[ch] = make_uint4(w01.x, dup_lo(w01.y), w01.y, dup_lo(w2));
            c1[ch] = make_uint4(__byte_perm(w01.x, w01.y, 0x5432), dup_lo(w01.y), __byte_perm(w01.y, w2, 0x5432), dup_lo(w2));
          }
        } else {
#pragma unroll
          for (int ch = 0; ch < 4; ch++) {
            const uint8_t* kc = smem + SM_KB + ch * KC_STRIDE * 2;
            const uint4 wv = *(const uint4*)(kc + (8 * n) * 2);
            const uint32_t w4 = *(const uint32_t*)(kc + (8 * n + 8) * 2);
            c0[ch] = make_uint4(__byte_perm(wv.x, wv.y, 0x5432), __byte_perm(wv.y, wv.z, 0x5432), __byte_perm(wv.z, wv.w, 0x5432), __byte_perm(wv.w, w4, 0x5432));
            c1[ch] = make_uint4(wv.y, wv.z, wv.w, (n == 31) ? dup_lo(w4) : w4);
          }
          if (lane < 8) {
            const int ch = lane >> 1, hi = lane & 1;
            const uint32_t k01 = *(const uint32_t*)(smem + SM_KB + ch * KC_STRIDE * 2);
            uint8_t* e = smem + SM_X + CV_E + ch * E_CH + hi * 16;
            *(uint4*)e = make_uint4(0, 0, 0, hi ? (k01 << 16) : 0u);
            *(uint4*)(e + E_COPY) = make_uint4(0, 0, 0, hi ? k01 : 0u);
          }
        }
#pragma unroll
        for (int ch = 0; ch < 4; ch++) {
          uint8_t* e = smem + SM_X + CV_E + ch * E_CH + (n + 2) * 16;
          *(uint4*)e = c0[ch];
          *(uint4*)(e + E_COPY) = c1[ch];
        }
      }
        fence_async();
        __syncwarp();
        if (lane == 0) mbar_arrive(bars + 8 * B_RRDY);
        TM_IF(wt == 0, 19);
      }
      if (lane == 0) {
        const uint32_t tag = ld_epoch() + 1;
        auto publish = [&](int s) {
          asm volatile("st.relaxed.gpu.global.u32 [%0], %1;" ::"l"(g_flag + ((it_ * 8 + ((jf + 1 + s) & 7)) * 8 + jf)), "r"(tag) : "memory");
          TM_IF(true, 3 + s);
        };
#pragma unroll 1
        for (int s = w; s < 7; s += 2) {
          if (s > 0) part_store(s);
          asm volatile("cp.async.bulk.wait_group.read 0;" ::: "memory");
          mbar_arrive(bars + 8 * (B_STF + s));
          if (s >= 2 && s < 6) {
            asm volatile("cp.async.bulk.wait_group 1;" ::: "memory");
            publish(s - 2);
          }
          if (s >= 4) {
            asm volatile("cp.async.bulk.wait_group 0;" ::: "memory");
            publish(s);
          }
        }
      }
      __syncwarp();
    }
    bar_sync(2, 128);
    if (tid == 256) {
      const uint32_t tk = atomicAdd(&g_exit, 1u);
      if (tk == NCTA - 1) {
        g_exit = 0;
        *(volatile uint32_t*)&g_epoch = ld_epoch() + 1;
      }
    }
    TM_IF(tid == 256, 13);
  } else {
    asm volatile("setmaxnreg.inc.sync.aligned.u32 200;");
    const int wg = warp >> 2;
    const int g = lane >> 2, q = lane & 3;
    const uint32_t dsk = *(const uint32_t*)(P.D_skip + d0 + 2 * wg);
    uint32_t hf[56];
    {
      float acc[128];
#pragma unroll
      for (int i = 0; i < 128; i++) zero_reg(acc[i]);
#pragma unroll 1
      for (int st = 0; st < 16; st++) {
        const int slot = st % 5;
        if ((st & 1) == 0) mbar_wait(bars + 8 * (B_XFULL + (st >> 1)), 0);
        mbar_wait(bars + 8 * (B_FULL + slot), (st / 5) & 1);
        const uint64_t da = mkdesc(sb + SM_X + (st >> 1) * 16384 + wg * 8192 + (st & 1) * 64, 16, 1024, 1);
        const uint64_t db = mkdesc(sb + SM_RING + slot * 16384, 4096, 1024, 1);
        wg_fence();
        wgmma_ss_n256(acc, da, db);
        wgmma_ss_n256(acc, da + 2, db + 128);
        wg_commit();
        if (st > 0) {
          wg_wait<1>();
          if (lane == 0) mbar_arrive(bars + 8 * (B_EMPTY + (st - 1) % 5));
        }
      }
      wg_wait<0>();
      if (lane == 0) mbar_arrive(bars + 8 * (B_EMPTY + 15 % 5));
#pragma unroll
      for (int m = 0; m < 16; m++) {
        hf[2 * m] = hmul2_bf16(pack_bf16(acc[4 * m], acc[4 * m + 1]), pack_bf16(acc[64 + 4 * m], acc[64 + 4 * m + 1]));
        hf[2 * m + 1] = hmul2_bf16(pack_bf16(acc[4 * m + 2], acc[4 * m + 3]), pack_bf16(acc[64 + 4 * m + 2], acc[64 + 4 * m + 3]));
      }
    }
    float accA[32], accB[32];
    auto issue_half = [&](float (&acc)[32], int s, auto half_tag) {
      constexpr int half = decltype(half_tag)::value;
      if (half == 0) {
#pragma unroll
        for (int i = 0; i < 32; i++) zero_reg(acc[i]);
      }
      const int st = 32 + 2 * s + half;
      const int slot = st % 5;
      mbar_wait(bars + 8 * (B_FULL + slot), (st / 5) & 1);
      uint32_t sbase;
      asm volatile("mov.b32 %0, %1;" : "=r"(sbase) : "r"(sb + SM_RING + slot * 16384));
      const uint64_t db = mkdesc(sbase, 1024, 1024, 1);
      wg_fence();
#pragma unroll
      for (int k = 0; k < 7; k++) {
        const int ks = 7 * half + k;
        wgmma_rs_n64t(acc, hf[4 * ks], hf[4 * ks + 1], hf[4 * ks + 2], hf[4 * ks + 3], db + k * 128);
      }
      wg_commit();
    };
    auto release = [&](int st) { if (lane == 0) mbar_arrive(bars + 8 * (B_EMPTY + st % 5)); };
    using H0 = IC<0>;
    using H1 = IC<1>;
    {
      float accg[48], accu[48];
#pragma unroll
      for (int i = 0; i < 48; i++) { zero_reg(accg[i]); zero_reg(accu[i]); }
      const uint32_t xrow = sb + SM_X + (wg * 64 + (warp & 3) * 16 + (lane & 15)) * 128;
      const uint32_t xsw = lane & 7, xhi = lane >> 4;
      uint32_t a0[4], a1[4], a2[4], a3[4];
#pragma unroll 1
      for (int kb = 0; kb < 8; kb++) {
        const uint32_t xb = xrow + kb * 16384;
        {
          const int st = 16 + 2 * kb, slot = st % 5;
          ldsm4(a0, xb + (((0 + xhi) ^ xsw) << 4));
          ldsm4(a1, xb + (((2 + xhi) ^ xsw) << 4));
          mbar_wait(bars + 8 * (B_FULL + slot), (st / 5) & 1);
          const uint64_t db = mkdesc(sb + SM_RING + slot * 16384, 4096, 1024, 1);
          wg_fence();
          wgmma_rs_n96(accg, a0[0], a0[1], a0[2], a0[3], db);
          wgmma_rs_n96(accu, a0[0], a0[1], a0[2], a0[3], db + 512);
          wgmma_rs_n96(accg, a1[0], a1[1], a1[2], a1[3], db + 128);
          wgmma_rs_n96(accu, a1[0], a1[1], a1[2], a1[3], db + 128 + 512);
          wg_commit();
          wg_wait<1>();
          if (kb > 0 && lane == 0) mbar_arrive(bars + 8 * (B_EMPTY + (st - 1) % 5));
        }
        {
          const int st = 17 + 2 * kb, slot = st % 5;
          ldsm4(a2, xb + (((4 + xhi) ^ xsw) << 4));
          ldsm4(a3, xb + (((6 + xhi) ^ xsw) << 4));
          mbar_wait(bars + 8 * (B_FULL + slot), (st / 5) & 1);
          const uint64_t db = mkdesc(sb + SM_RING + slot * 16384, 4096, 1024, 1);
          wg_fence();
          wgmma_rs_n96(accg, a2[0], a2[1], a2[2], a2[3], db);
          wgmma_rs_n96(accu, a2[0], a2[1], a2[2], a2[3], db + 512);
          wgmma_rs_n96(accg, a3[0], a3[1], a3[2], a3[3], db + 128);
          wgmma_rs_n96(accu, a3[0], a3[1], a3[2], a3[3], db + 128 + 512);
          wg_commit();
          wg_wait<1>();
          if (lane == 0) mbar_arrive(bars + 8 * (B_EMPTY + (st - 1) % 5));
        }
      }
      issue_half(accA, 0, H0{});
      wg_wait<1>();
      if (lane == 0) { mbar_arrive(bars + 8 * (B_EMPTY + 31 % 5)); mbar_arrive(bars + 8 * (B_XFREE + 7)); }
#pragma unroll
      for (int m = 0; m < 12; m++) {
        hf[32 + 2 * m] = hmul2_bf16(pack_bf16(accg[4 * m], accg[4 * m + 1]), pack_bf16(accu[4 * m], accu[4 * m + 1]));
        hf[32 + 2 * m + 1] = hmul2_bf16(pack_bf16(accg[4 * m + 2], accg[4 * m + 3]), pack_bf16(accu[4 * m + 2], accu[4 * m + 3]));
      }
    }
    auto send_pass = [&](float (&acc)[32], int s) {
      uint4* dst = (uint4*)(smem + SM_X + (s == 6 ? CV_E + 2 * wg * E_CH : CV_S + wg * S_WG + (s & 3) * 8192) + (warp & 3) * 2048) + lane;
#pragma unroll
      for (int c = 0; c < 4; c++) {
        uint4 v;
        v.x = pack_bf16(acc[8 * c], acc[8 * c + 1]); v.y = pack_bf16(acc[8 * c + 2], acc[8 * c + 3]);
        v.z = pack_bf16(acc[8 * c + 4], acc[8 * c + 5]); v.w = pack_bf16(acc[8 * c + 6], acc[8 * c + 7]);
        dst[c * 32] = v;
      }
      fence_async();
      __syncwarp();
      if (lane == 0) mbar_arrive(bars + 8 * (B_SENT + s));
    };
    auto part_load = [&](uint4 (&v)[4], int k) {
      const uint4* sp = g_part + (size_t)(((it_ * 8 + jf) * 8 + ((jf - k) & 7)) * 8 + warp) * 128 + lane;
#pragma unroll
      for (int c = 0; c < 4; c++) v[c] = ld_cg4(sp + c * 32);
    };
    auto part_add = [&](const uint4 (&v)[4]) {
#pragma unroll
      for (int c = 0; c < 4; c++) {
        accA[8 * c] += bf_lo(v[c].x); accA[8 * c + 1] += bf_hi(v[c].x); accA[8 * c + 2] += bf_lo(v[c].y); accA[8 * c + 3] += bf_hi(v[c].y);
        accA[8 * c + 4] += bf_lo(v[c].z); accA[8 * c + 5] += bf_hi(v[c].z); accA[8 * c + 6] += bf_lo(v[c].w); accA[8 * c + 7] += bf_hi(v[c].w);
      }
    };
    issue_half(accA, 0, H1{}); wg_wait<1>(); release(32);
    mbar_wait(bars + 8 * (B_XFREE + 7), 0);
    issue_half(accB, 1, H0{}); wg_wait<1>(); release(33); send_pass(accA, 0);
    issue_half(accB, 1, H1{}); wg_wait<1>(); release(34);
    issue_half(accA, 2, H0{}); wg_wait<1>(); release(35); send_pass(accB, 1);
    issue_half(accA, 2, H1{}); wg_wait<1>(); release(36);
    issue_half(accB, 3, H0{}); wg_wait<1>(); release(37); send_pass(accA, 2);
    issue_half(accB, 3, H1{}); wg_wait<1>(); release(38);
    issue_half(accA, 4, H0{}); wg_wait<1>(); release(39); send_pass(accB, 3);
    issue_half(accA, 4, H1{}); wg_wait<1>(); release(40);
    issue_half(accB, 5, H0{}); wg_wait<1>(); release(41); mbar_wait(bars + 8 * (B_STF + 0), 0); send_pass(accA, 4);
    issue_half(accB, 5, H1{}); wg_wait<1>(); release(42);
    wg_wait<0>(); mbar_wait(bars + 8 * (B_STF + 1), 0); send_pass(accB, 5);
    {
      TM_IF(tid == 0, 10);
      const int w = warp & 3;
      mbar_wait(bars + 8 * B_RRDY, 0);
      TM_IF(tid == 0, 11);
      const uint32_t zero = lds32(sb + SM_X + CV_R + (2 * wg + 1) * R_CH + 128 * 16);
      const int c = tid & 127;
      const float* Sr = (const float*)(smem + SM_X + CV_S + wg * S_WG) + (127 - c);
      float* Sw = (float*)(smem + SM_X + CV_S + wg * S_WG) + w * 16 * S_PITCH + g * S_PITCH + 2 * q;
      uint32_t fa[4][4], fb[4][4];
      uint32_t ares[8] = {0, 0, 0, 0, 0, 0, 0, 0}, rv[8];
      auto load_u = [&](int ch) {
        const uint4 r0v = *(const uint4*)(smem + SM_X + CV_R + ch * R_CH + (127 - c) * 16);
        const uint4 r1v = *(const uint4*)(smem + SM_X + CV_R + ch * R_CH + R_HALF + (127 - c) * 16);
        rv[0] = r0v.x; rv[1] = r0v.y; rv[2] = r0v.z; rv[3] = r0v.w; rv[4] = r1v.x; rv[5] = r1v.y; rv[6] = r1v.z; rv[7] = r1v.w;
      };
#define POST(r2, dk2)                                                                              \
      {                                                                                            \
        float y_[2];                                                                               \
        _Pragma("unroll") for (int t2 = 0; t2 < 2; t2++) {                                         \
          const int r0 = 2 * (r2) + t2;                                                            \
          const float s1 = c >= 1 ? Sr[(16 + r0) * S_PITCH + 1] : 0.f;                             \
          const float s2 = c >= 2 ? Sr[(32 + r0) * S_PITCH + 2] : 0.f;                             \
          const float s3 = c >= 3 ? Sr[(48 + r0) * S_PITCH + 3] : 0.f;                             \
          y_[t2] = (Sr[r0 * S_PITCH] + s1) + (s2 + s3);                                            \
        }                                                                                          \
        ares[r2] = hadd2_bf16(pack_bf16(y_[0], y_[1]), hmul2_bf16(__byte_perm(rv[7 - (r2)], rv[7 - (r2)], 0x1032), dk2)); \
      }
      auto store_a = [&](int ch) {
        uint4* ap = (uint4*)(smem + SM_X + CV_R + ch * R_CH + c * 32);
        ap[0] = make_uint4(ares[0], ares[1], ares[2], ares[3]);
        ap[1] = make_uint4(ares[4], ares[5], ares[6], ares[7]);
        fence_async();
      };
      const uint32_t eoff = ((g & 1) ? E_COPY : 0) + (16 * w + (g & ~1) + 2 * q) * 2;
      const uint32_t dkA = dup_lo(dsk), dkB = dup_hi(dsk);
      {
        const int ch = 2 * wg;
        const uint32_t ebase = sb + SM_X + CV_E + ch * E_CH + eoff;
        const uint64_t de = mkdesc(sb + SM_X + CV_R + ch * R_CH, R_HALF, 128, 0);
        conv_load4<0>(fa, ebase, zero);
        conv_load4<4>(fb, ebase, zero);
        CONV_CHANNEL(mbar_wait(bars + 8 * (B_STF + 2), 0); mbar_wait(bars + 8 * (B_STF + 3), 0); mbar_wait(bars + 8 * (B_STF + 4), 0); mbar_wait(bars + 8 * (B_STF + 5), 0);, , )
        TM_IF(tid == 0, 14);
      }
      issue_half(accA, 6, H0{});
      issue_half(accA, 6, H1{});
      bar_sync(6 + wg, 128);
      POST(0, dkA) POST(1, dkA) POST(2, dkA) POST(3, dkA) POST(4, dkA) POST(5, dkA) POST(6, dkA) POST(7, dkA)
      store_a(2 * wg);
      __syncwarp();
      if (lane == 0) mbar_arrive(bars + 8 * B_ADONE);
      {
        const int ch = 2 * wg + 1;
        const uint32_t ebase = sb + SM_X + CV_E + ch * E_CH + eoff;
        const uint64_t de = mkdesc(sb + SM_X + CV_R + ch * R_CH, R_HALF, 128, 0);
        conv_load4<0>(fa, ebase, zero);
        conv_load4<4>(fb, ebase, zero);
        wg_wait<0>();
        send_pass(accA, 6);
        CONV_CHANNEL(bar_sync(6 + wg, 128);, , )
        bar_sync(6 + wg, 128);
        TM_IF(tid == 0, 17);
        POST(0, dkB) POST(1, dkB) POST(2, dkB) POST(3, dkB) POST(4, dkB) POST(5, dkB) POST(6, dkB) POST(7, dkB)
        store_a(ch);
        __syncwarp();
        if (lane == 0) mbar_arrive(bars + 8 * B_ADONE);
      }
#undef POST
    }
    {
      uint4 v0[4], v1[4], v2[4], v3[4];
      mbar_wait(bars + 8 * B_GOT, 0);
      part_load(v0, 1);
      part_load(v1, 2);
      part_load(v2, 3);
      part_load(v3, 4);
      issue_half(accB, 7, H0{});
      issue_half(accB, 7, H1{});
#pragma unroll
      for (int i = 0; i < 32; i++) accA[i] = 0.f;
      part_add(v0); part_load(v0, 5);
      part_add(v1); part_load(v1, 6);
      part_add(v2); part_load(v2, 7);
      part_add(v3);
      part_add(v0);
      part_add(v1);
      part_add(v2);
    }
    TM_IF(tid == 0, 28);
    mbar_wait(bars + 8 * B_ATILE, 0);
    TM_IF(tid == 0, 29);
    const int row0 = it_ * 128 + warp * 16 + g;
    const float g0 = __ldcg(g_gate + row0), g1 = __ldcg(g_gate + row0 + 8);
    uint32_t av[16];
    {
      const int dl = (lane & 7) + ((lane >> 4) << 3);
      const int chunk = 2 * (warp & 3) + ((lane >> 3) & 1);
      const uint32_t abase = sb + SM_AT + wg * 8192 + dl * 128 + ((chunk ^ (lane & 7)) << 4);
#pragma unroll
      for (int m2 = 0; m2 < 4; m2++) {
        asm volatile("ldmatrix.sync.aligned.m8n8.x4.trans.shared.b16 {%0,%1,%2,%3}, [%4];"
                     : "=r"(av[4 * m2]), "=r"(av[4 * m2 + 1]), "=r"(av[4 * m2 + 2]), "=r"(av[4 * m2 + 3]) : "r"(abase + m2 * 2048) : "memory");
      }
    }
    wg_wait<0>();
    const uint32_t gg0 = pack_bf16(g0, g0), gg1 = pack_bf16(g1, g1);
    const uint32_t og0 = pack_bf16(1.f - g0, 1.f - g0), og1 = pack_bf16(1.f - g1, 1.f - g1);
    uint32_t ov[16];
#pragma unroll
    for (int m = 0; m < 8; m++) {
      const uint32_t b0 = pack_bf16(accA[4 * m] + accB[4 * m], accA[4 * m + 1] + accB[4 * m + 1]);
      const uint32_t b1 = pack_bf16(accA[4 * m + 2] + accB[4 * m + 2], accA[4 * m + 3] + accB[4 * m + 3]);
      ov[2 * m] = hadd2_bf16(hmul2_bf16(gg0, av[2 * m]), hmul2_bf16(og0, b0));
      ov[2 * m + 1] = hadd2_bf16(hmul2_bf16(gg1, av[2 * m + 1]), hmul2_bf16(og1, b1));
    }
    {
      const uint32_t ob = sb + SM_X + CV_S + wg * S_WG + (warp & 3) * 2048;
      const int srow = (lane & 7) + ((lane >> 3) & 1) * 8;
#pragma unroll
      for (int m2 = 0; m2 < 4; m2++) {
        const int chunk = 2 * m2 + (lane >> 4);
        asm volatile("stmatrix.sync.aligned.m8n8.x4.shared.b16 [%0], {%1,%2,%3,%4};"
                     ::"r"(ob + srow * 128 + ((chunk ^ (srow & 7)) << 4)), "r"(ov[4 * m2]), "r"(ov[4 * m2 + 1]), "r"(ov[4 * m2 + 2]), "r"(ov[4 * m2 + 3]) : "memory");
      }
      __syncwarp();
#pragma unroll
      for (int i = 0; i < 4; i++) {
        const int r = 4 * i + (lane >> 3), chunk = lane & 7;
        const uint4 v = *(const uint4*)(smem + SM_X + CV_S + wg * S_WG + (warp & 3) * 2048 + r * 128 + ((chunk ^ (r & 7)) << 4));
        *(uint4*)(P.out + (it_ * 128 + warp * 16 + r) * D_ + jf * 64 + chunk * 8) = v;
      }
    }
    TM_IF(tid == 0, 30);
  }
}

typedef CUresult (*EncFn)(CUtensorMap*, CUtensorMapDataType, cuuint32_t, void*, const cuuint64_t*, const cuuint64_t*, const cuuint32_t*,
                          const cuuint32_t*, CUtensorMapInterleave, CUtensorMapSwizzle, CUtensorMapL2promotion, CUtensorMapFloatOOBfill);

struct HostState {
  bool ready;
  const void* key[4];
  Maps M;
};
HostState hs;

}

extern "C" void kernel_launch(void* const* d_in, const int* in_sizes, int n_in, void* d_out, int out_size) {
  (void)in_sizes; (void)n_in; (void)out_size;
  void* x = d_in[0];
  void* wg = d_in[8];
  void* wu = d_in[9];
  void* wd = d_in[10];
  if (!hs.ready || hs.key[0] != x || hs.key[1] != wg || hs.key[2] != wu || hs.key[3] != wd) {
    void* fn = nullptr;
    cudaDriverEntryPointQueryResult qr;
    cudaGetDriverEntryPoint("cuTensorMapEncodeTiled", &fn, cudaEnableDefault, &qr);
    EncFn enc = (EncFn)fn;
    const cuuint32_t es[3] = {1, 1, 1};
    const CUtensorMapDataType BF = CU_TENSOR_MAP_DATA_TYPE_BFLOAT16;
    const CUtensorMapInterleave IN = CU_TENSOR_MAP_INTERLEAVE_NONE;
    const CUtensorMapL2promotion PR = CU_TENSOR_MAP_L2_PROMOTION_L2_128B;
    const CUtensorMapFloatOOBfill OO = CU_TENSOR_MAP_FLOAT_OOB_FILL_NONE;
    {
      cuuint64_t gd[2] = {(cuuint64_t)D_, (cuuint64_t)L_}; cuuint64_t gs[1] = {(cuuint64_t)D_ * 2}; cuuint32_t box[2] = {64, 128};
      enc(&hs.M.X, BF, 2, x, gd, gs, box, es, IN, CU_TENSOR_MAP_SWIZZLE_128B, PR, OO);
    }
    {
      cuuint64_t gd[2] = {(cuuint64_t)F_, (cuuint64_t)D_}; cuuint64_t gs[1] = {(cuuint64_t)F_ * 2}; cuuint32_t box[2] = {64, 32};
      enc(&hs.M.Wg, BF, 2, wg, gd, gs, box, es, IN, CU_TENSOR_MAP_SWIZZLE_128B, PR, OO);
      enc(&hs.M.Wu, BF, 2, wu, gd, gs, box, es, IN, CU_TENSOR_MAP_SWIZZLE_128B, PR, OO);
      for (int o = 0; o < 2; o++) {
        cuuint64_t gd3[3] = {64, (cuuint64_t)D_, (cuuint64_t)(F_ / 64 - o)}; cuuint64_t gs3[2] = {(cuuint64_t)F_ * 2, 128};
        cuuint32_t box3[3] = {64, 32, 2};
        enc(&hs.M.Wg3[o], BF, 3, (char*)wg + 64 * o, gd3, gs3, box3, es, IN, CU_TENSOR_MAP_SWIZZLE_128B, PR, OO);
        enc(&hs.M.Wu3[o], BF, 3, (char*)wu + 64 * o, gd3, gs3, box3, es, IN, CU_TENSOR_MAP_SWIZZLE_128B, PR, OO);
      }
    }
    {
      cuuint64_t gd[2] = {(cuuint64_t)D_, (cuuint64_t)F_}; cuuint64_t gs[1] = {(cuuint64_t)D_ * 2}; cuuint32_t box[2] = {64, 112};
      enc(&hs.M.Wd, BF, 2, wd, gd, gs, box, es, IN, CU_TENSOR_MAP_SWIZZLE_128B, PR, OO);
    }
    {
      void* pa = nullptr;
      cudaGetSymbolAddress(&pa, g_aT);
      cuuint64_t gd[2] = {(cuuint64_t)L_, (cuuint64_t)D_}; cuuint64_t gs[1] = {(cuuint64_t)L_ * 2}; cuuint32_t box[2] = {64, 64};
      enc(&hs.M.AT, BF, 2, pa, gd, gs, box, es, IN, CU_TENSOR_MAP_SWIZZLE_128B, PR, OO);
    }
    cudaFuncSetAttribute(fused_kernel, cudaFuncAttributeMaxDynamicSharedMemorySize, SM_TOTAL);
    hs.key[0] = x; hs.key[1] = wg; hs.key[2] = wu; hs.key[3] = wd;
    hs.ready = true;
  }
  Params P;
  P.x = (const __nv_bfloat16*)d_in[0];
  P.log_A_real = (const __nv_bfloat16*)d_in[1];
  P.A_imag = (const __nv_bfloat16*)d_in[2];
  P.C_real = (const __nv_bfloat16*)d_in[3];
  P.C_imag = (const __nv_bfloat16*)d_in[4];
  P.log_dt = (const __nv_bfloat16*)d_in[5];
  P.D_skip = (const __nv_bfloat16*)d_in[6];
  P.gate_w = (const __nv_bfloat16*)d_in[11];
  P.w_gate = (const __nv_bfloat16*)wg;
  P.w_up = (const __nv_bfloat16*)wu;
  P.w_down = (const __nv_bfloat16*)wd;
  P.out = (__nv_bfloat16*)d_out;
  fused_kernel<<<NCTA, NTHREADS, SM_TOTAL>>>(hs.M, P);
}
```

```cpp
#include <cuda_runtime.h>
#include <cuda_bf16.h>
#include <cuda.h>
#include <stdint.h>

#define PUBMODE 2
namespace {

constexpr int L_ = 2048, D_ = 512, F_ = 1792, NS_ = 128;
constexpr int NCTA = 128;
constexpr int NTHREADS = 384;

constexpr int SM_X = 0;
constexpr int SM_RING = 131072;
constexpr int KC_STRIDE = 656;
constexpr int SM_KB = 212992;
constexpr int SM_PR = SM_KB + 4 * KC_STRIDE * 2;
constexpr int SM_BAR = SM_PR + 512 * 24;
constexpr int SM_TOTAL = SM_BAR + 512;
constexpr int CV_R = 0;
constexpr int R_HALF = 156 * 16;
constexpr int R_CH = 2 * R_HALF;
constexpr int CV_E = 4 * R_CH;
constexpr int E_COPY = 4160;
constexpr int E_CH = 2 * E_COPY;
constexpr int CV_S = CV_E + 4 * E_CH;
constexpr int S_PITCH = 136;
constexpr int S_WG = 4 * 16 * S_PITCH * 4;
constexpr int SM_AT = SM_X;
static_assert(CV_S + 2 * S_WG + 8192 <= 131072, "conv region");
static_assert(SM_PR % 128 == 0, "alignment");

constexpr int B_FULL = 0, B_EMPTY = 5, B_XFULL = 10, B_XFREE = 18, B_ATILE = 26, B_RRDY = 27, B_ADONE = 28, B_KPART = 29, B_KSUM = 30, B_SENT = 35, B_GOT = 43, B_STF = 51;

__device__ uint4 g_part[16 * 8 * 8 * 8 * 4 * 32];
__device__ uint32_t g_flag[16 * 8 * 8];
__device__ __align__(1024) __nv_bfloat16 g_aT[D_ * L_];
__device__ float g_gate[L_];
__device__ uint32_t g_done1;
__device__ uint32_t g_cnt[8 * 32];
__device__ uint32_t g_exit;
__device__ uint32_t g_zero;
__device__ uint32_t g_epoch;

#define TM_IF(cond, idx) do {} while (0)
#define FAIL(a, ph) break
#define SPIN_LIMIT (1 << 22)
#define MBAR_LIMIT (1 << 20)
__device__ __forceinline__ uint32_t smem_u32(const void* p) { return (uint32_t)__cvta_generic_to_shared(p); }
__device__ __forceinline__ void mbar_init(uint32_t a, uint32_t c) { asm volatile("mbarrier.init.shared::cta.b64 [%0], %1;" ::"r"(a), "r"(c) : "memory"); }
__device__ __forceinline__ void mbar_expect(uint32_t a, uint32_t bytes) { asm volatile("mbarrier.arrive.expect_tx.shared::cta.b64 _, [%0], %1;" ::"r"(a), "r"(bytes) : "memory"); }
__device__ __forceinline__ void mbar_arrive(uint32_t a) { asm volatile("mbarrier.arrive.shared::cta.b64 _, [%0];" ::"r"(a) : "memory"); }
__device__ __forceinline__ void mbar_wait(uint32_t a, uint32_t ph) {
  asm volatile("{\n.reg .pred p;\n.reg .u32 c;\nmov.u32 c, 0;\nLW:\nmbarrier.try_wait.parity.shared::cta.b64 p, [%0], %1, %2;\n@p bra LD;\n"
               "add.u32 c, c, 1;\nsetp.lt.u32 p, c, 1048576;\n@p bra LW;\nLD:\n}" ::"r"(a), "r"(ph), "r"(20000u) : "memory");
}
template <int NS> __device__ __forceinline__ void mbar_wait_lazy(uint32_t a, uint32_t ph) {
  asm volatile("{\n.reg .pred p;\n.reg .u32 c;\nmov.u32 c, 0;\nLW:\nmbarrier.test_wait.parity.shared::cta.b64 p, [%0], %1;\n@p bra LD;\n"
               "nanosleep.u32 %2;\nadd.u32 c, c, 1;\nsetp.lt.u32 p, c, 4194304;\n@p bra LW;\nLD:\n}" ::"r"(a), "r"(ph), "n"(NS) : "memory");
}
__device__ __forceinline__ void tma2d(uint32_t dst, const CUtensorMap* m, int c0, int c1, uint32_t bar) {
  asm volatile("cp.async.bulk.tensor.2d.shared::cluster.global.mbarrier::complete_tx::bytes [%0], [%1, {%3,%4}], [%2];" ::"r"(dst), "l"(m), "r"(bar), "r"(c0), "r"(c1) : "memory");
}
__device__ __forceinline__ void tma3d(uint32_t dst, const CUtensorMap* m, int c0, int c1, int c2, uint32_t bar) {
  asm volatile("cp.async.bulk.tensor.3d.shared::cluster.global.mbarrier::complete_tx::bytes [%0], [%1, {%3,%4,%5}], [%2];" ::"r"(dst), "l"(m), "r"(bar), "r"(c0), "r"(c1), "r"(c2) : "memory");
}
__device__ __forceinline__ uint64_t mkdesc(uint32_t addr, uint32_t lbo, uint32_t sbo, uint32_t sw) {
  return (uint64_t)((addr & 0x3FFFF) >> 4) | ((uint64_t)(lbo >> 4) << 16) | ((uint64_t)(sbo >> 4) << 32) | ((uint64_t)sw << 62);
}
__device__ __forceinline__ void wg_fence() { asm volatile("wgmma.fence.sync.aligned;" ::: "memory"); }
__device__ __forceinline__ void wg_commit() { asm volatile("wgmma.commit_group.sync.aligned;" ::: "memory"); }
template <int N> __device__ __forceinline__ void wg_wait() { asm volatile("wgmma.wait_group.sync.aligned %0;" ::"n"(N) : "memory"); }
__device__ __forceinline__ void zero_reg(float& x) { asm volatile("mov.f32 %0, 0f00000000;" : "=f"(x)); }
__device__ __forceinline__ void movf(float& d, float s) { asm volatile("mov.f32 %0, %1;" : "=f"(d) : "f"(s)); }
__device__ __forceinline__ void bar_sync(int id, int n) { asm volatile("bar.sync %0, %1;" ::"r"(id), "r"(n) : "memory"); }
__device__ __forceinline__ void fence_async() { asm volatile("fence.proxy.async.shared::cta;" ::: "memory"); }
__device__ __forceinline__ uint32_t pack_bf16(float lo, float hi) {
  uint32_t r;
  asm("cvt.rn.bf16x2.f32 %0, %1, %2;" : "=r"(r) : "f"(hi), "f"(lo));
  return r;
}
__device__ __forceinline__ uint32_t hmul2_bf16(uint32_t a, uint32_t b) {
  uint32_t r;
  asm("mul.rn.bf16x2 %0, %1, %2;" : "=r"(r) : "r"(a), "r"(b));
  return r;
}
__device__ __forceinline__ uint32_t hadd2_bf16(uint32_t a, uint32_t b) {
  uint32_t r;
  asm("add.rn.bf16x2 %0, %1, %2;" : "=r"(r) : "r"(a), "r"(b));
  return r;
}
__device__ __forceinline__ float bf_lo(uint32_t v) { return __uint_as_float(v << 16); }
__device__ __forceinline__ float bf_hi(uint32_t v) { return __uint_as_float(v & 0xFFFF0000u); }
__device__ __forceinline__ float bf16r(float x) { return __bfloat162float(__float2bfloat16_rn(x)); }
__device__ __forceinline__ float ldbf(const __nv_bfloat16* p) { return __bfloat162float(*p); }
__device__ __forceinline__ uint32_t ld_acquire(const uint32_t* p) {
  uint32_t v;
  asm volatile("ld.acquire.gpu.global.u32 %0, [%1];" : "=r"(v) : "l"(p) : "memory");
  return v;
}
__device__ __forceinline__ void st_release(uint32_t* p, uint32_t v) { asm volatile("st.release.gpu.global.u32 [%0], %1;" ::"l"(p), "r"(v) : "memory"); }
__device__ __forceinline__ uint4 ld_cg4(const uint4* p) {
  uint4 v;
  asm volatile("ld.global.cg.v4.u32 {%0,%1,%2,%3}, [%4];" : "=r"(v.x), "=r"(v.y), "=r"(v.z), "=r"(v.w) : "l"(p) : "memory");
  return v;
}
__device__ __forceinline__ uint32_t ld_cg1(const void* p) {
  uint32_t v;
  asm volatile("ld.global.cg.u32 %0, [%1];" : "=r"(v) : "l"(p) : "memory");
  return v;
}
__device__ __forceinline__ uint32_t lds32(uint32_t a) {
  uint32_t v;
  asm volatile("ld.shared.u32 %0, [%1];" : "=r"(v) : "r"(a) : "memory");
  return v;
}
__device__ __forceinline__ void ldsm4(uint32_t (&r)[4], uint32_t a) {
  asm volatile("ldmatrix.sync.aligned.m8n8.x4.shared.b16 {%0,%1,%2,%3}, [%4];" : "=r"(r[0]), "=r"(r[1]), "=r"(r[2]), "=r"(r[3]) : "r"(a) : "memory");
}
__device__ __forceinline__ uint32_t pack_f16(float lo, float hi) {
  uint32_t r;
  asm("cvt.rn.f16x2.f32 %0, %1, %2;" : "=r"(r) : "f"(hi), "f"(lo));
  return r;
}

__device__ __forceinline__ void wgmma_ss_n256(float (&d)[128], uint64_t da, uint64_t db) {
  asm volatile("wgmma.mma_async.sync.aligned.m64n256k16.f32.bf16.bf16 {%0, %1, %2, %3, %4, %5, %6, %7, %8, %9, %10, %11, %12, %13, %14, %15, %16, %17, %18, %19, %20, %21, %22, %23, %24, %25, %26, %27, %28, %29, %30, %31, %32, %33, %34, %35, %36, %37, %38, %39, %40, %41, %42, %43, %44, %45, %46, %47, %48, %49, %50, %51, %52, %53, %54, %55, %56, %57, %58, %59, %60, %61, %62, %63, %64, %65, %66, %67, %68, %69, %70, %71, %72, %73, %74, %75, %76, %77, %78, %79, %80, %81, %82, %83, %84, %85, %86, %87, %88, %89, %90, %91, %92, %93, %94, %95, %96, %97, %98, %99, %100, %101, %102, %103, %104, %105, %106, %107, %108, %109, %110, %111, %112, %113, %114, %115, %116, %117, %118, %119, %120, %121, %122, %123, %124, %125, %126, %127}, %128, %129, 1, 1, 1, 0, 1;"
    : "+f"(d[0]), "+f"(d[1]), "+f"(d[2]), "+f"(d[3]), "+f"(d[4]), "+f"(d[5]), "+f"(d[6]), "+f"(d[7]), "+f"(d[8]), "+f"(d[9]), "+f"(d[10]), "+f"(d[11]), "+f"(d[12]), "+f"(d[13]), "+f"(d[14]), "+f"(d[15]), "+f"(d[16]), "+f"(d[17]), "+f"(d[18]), "+f"(d[19]), "+f"(d[20]), "+f"(d[21]), "+f"(d[22]), "+f"(d[23]), "+f"(d[24]), "+f"(d[25]), "+f"(d[26]), "+f"(d[27]), "+f"(d[28]), "+f"(d[29]), "+f"(d[30]), "+f"(d[31]), "+f"(d[32]), "+f"(d[33]), "+f"(d[34]), "+f"(d[35]), "+f"(d[36]), "+f"(d[37]), "+f"(d[38]), "+f"(d[39]), "+f"(d[40]), "+f"(d[41]), "+f"(d[42]), "+f"(d[43]), "+f"(d[44]), "+f"(d[45]), "+f"(d[46]), "+f"(d[47]), "+f"(d[48]), "+f"(d[49]), "+f"(d[50]), "+f"(d[51]), "+f"(d[52]), "+f"(d[53]), "+f"(d[54]), "+f"(d[55]), "+f"(d[56]), "+f"(d[57]), "+f"(d[58]), "+f"(d[59]), "+f"(d[60]), "+f"(d[61]), "+f"(d[62]), "+f"(d[63]), "+f"(d[64]), "+f"(d[65]), "+f"(d[66]), "+f"(d[67]), "+f"(d[68]), "+f"(d[69]), "+f"(d[70]), "+f"(d[71]), "+f"(d[72]), "+f"(d[73]), "+f"(d[74]), "+f"(d[75]), "+f"(d[76]), "+f"(d[77]), "+f"(d[78]), "+f"(d[79]), "+f"(d[80]), "+f"(d[81]), "+f"(d[82]), "+f"(d[83]), "+f"(d[84]), "+f"(d[85]), "+f"(d[86]), "+f"(d[87]), "+f"(d[88]), "+f"(d[89]), "+f"(d[90]), "+f"(d[91]), "+f"(d[92]), "+f"(d[93]), "+f"(d[94]), "+f"(d[95]), "+f"(d[96]), "+f"(d[97]), "+f"(d[98]), "+f"(d[99]), "+f"(d[100]), "+f"(d[101]), "+f"(d[102]), "+f"(d[103]), "+f"(d[104]), "+f"(d[105]), "+f"(d[106]), "+f"(d[107]), "+f"(d[108]), "+f"(d[109]), "+f"(d[110]), "+f"(d[111]), "+f"(d[112]), "+f"(d[113]), "+f"(d[114]), "+f"(d[115]), "+f"(d[116]), "+f"(d[117]), "+f"(d[118]), "+f"(d[119]), "+f"(d[120]), "+f"(d[121]), "+f"(d[122]), "+f"(d[123]), "+f"(d[124]), "+f"(d[125]), "+f"(d[126]), "+f"(d[127]) : "l"(da), "l"(db));
}
__device__ __forceinline__ void wgmma_rs_n96(float (&d)[48], uint32_t a0, uint32_t a1, uint32_t a2, uint32_t a3, uint64_t db) {
  asm volatile("wgmma.mma_async.sync.aligned.m64n96k16.f32.bf16.bf16 {%0, %1, %2, %3, %4, %5, %6, %7, %8, %9, %10, %11, %12, %13, %14, %15, %16, %17, %18, %19, %20, %21, %22, %23, %24, %25, %26, %27, %28, %29, %30, %31, %32, %33, %34, %35, %36, %37, %38, %39, %40, %41, %42, %43, %44, %45, %46, %47}, {%48,%49,%50,%51}, %52, 1, 1, 1, 1;"
    : "+f"(d[0]), "+f"(d[1]), "+f"(d[2]), "+f"(d[3]), "+f"(d[4]), "+f"(d[5]), "+f"(d[6]), "+f"(d[7]), "+f"(d[8]), "+f"(d[9]), "+f"(d[10]), "+f"(d[11]), "+f"(d[12]), "+f"(d[13]), "+f"(d[14]), "+f"(d[15]), "+f"(d[16]), "+f"(d[17]), "+f"(d[18]), "+f"(d[19]), "+f"(d[20]), "+f"(d[21]), "+f"(d[22]), "+f"(d[23]), "+f"(d[24]), "+f"(d[25]), "+f"(d[26]), "+f"(d[27]), "+f"(d[28]), "+f"(d[29]), "+f"(d[30]), "+f"(d[31]), "+f"(d[32]), "+f"(d[33]), "+f"(d[34]), "+f"(d[35]), "+f"(d[36]), "+f"(d[37]), "+f"(d[38]), "+f"(d[39]), "+f"(d[40]), "+f"(d[41]), "+f"(d[42]), "+f"(d[43]), "+f"(d[44]), "+f"(d[45]), "+f"(d[46]), "+f"(d[47]) : "r"(a0), "r"(a1), "r"(a2), "r"(a3), "l"(db));
}
__device__ __forceinline__ void wgmma_rs_n64t(float (&d)[32], uint32_t a0, uint32_t a1, uint32_t a2, uint32_t a3, uint64_t db) {
  asm volatile("wgmma.mma_async.sync.aligned.m64n64k16.f32.bf16.bf16 {%0, %1, %2, %3, %4, %5, %6, %7, %8, %9, %10, %11, %12, %13, %14, %15, %16, %17, %18, %19, %20, %21, %22, %23, %24, %25, %26, %27, %28, %29, %30, %31}, {%32,%33,%34,%35}, %36, 1, 1, 1, 1;"
    : "+f"(d[0]), "+f"(d[1]), "+f"(d[2]), "+f"(d[3]), "+f"(d[4]), "+f"(d[5]), "+f"(d[6]), "+f"(d[7]), "+f"(d[8]), "+f"(d[9]), "+f"(d[10]), "+f"(d[11]), "+f"(d[12]), "+f"(d[13]), "+f"(d[14]), "+f"(d[15]), "+f"(d[16]), "+f"(d[17]), "+f"(d[18]), "+f"(d[19]), "+f"(d[20]), "+f"(d[21]), "+f"(d[22]), "+f"(d[23]), "+f"(d[24]), "+f"(d[25]), "+f"(d[26]), "+f"(d[27]), "+f"(d[28]), "+f"(d[29]), "+f"(d[30]), "+f"(d[31]) : "r"(a0), "r"(a1), "r"(a2), "r"(a3), "l"(db));
}
__device__ __forceinline__ void cw128z(float (&d)[64], uint32_t a0, uint32_t a1, uint32_t a2, uint32_t a3, uint64_t db) {
  asm volatile("{.reg .pred p; setp.ne.b32 p, 0, 0; wgmma.mma_async.sync.aligned.m64n128k16.f32.bf16.bf16 {%0, %1, %2, %3, %4, %5, %6, %7, %8, %9, %10, %11, %12, %13, %14, %15, %16, %17, %18, %19, %20, %21, %22, %23, %24, %25, %26, %27, %28, %29, %30, %31, %32, %33, %34, %35, %36, %37, %38, %39, %40, %41, %42, %43, %44, %45, %46, %47, %48, %49, %50, %51, %52, %53, %54, %55, %56, %57, %58, %59, %60, %61, %62, %63}, {%64,%65,%66,%67}, %68, p, 1, 1, 0;}"
    : "=f"(d[0]), "=f"(d[1]), "=f"(d[2]), "=f"(d[3]), "=f"(d[4]), "=f"(d[5]), "=f"(d[6]), "=f"(d[7]), "=f"(d[8]), "=f"(d[9]), "=f"(d[10]), "=f"(d[11]), "=f"(d[12]), "=f"(d[13]), "=f"(d[14]), "=f"(d[15]), "=f"(d[16]), "=f"(d[17]), "=f"(d[18]), "=f"(d[19]), "=f"(d[20]), "=f"(d[21]), "=f"(d[22]), "=f"(d[23]), "=f"(d[24]), "=f"(d[25]), "=f"(d[26]), "=f"(d[27]), "=f"(d[28]), "=f"(d[29]), "=f"(d[30]), "=f"(d[31]), "=f"(d[32]), "=f"(d[33]), "=f"(d[34]), "=f"(d[35]), "=f"(d[36]), "=f"(d[37]), "=f"(d[38]), "=f"(d[39]), "=f"(d[40]), "=f"(d[41]), "=f"(d[42]), "=f"(d[43]), "=f"(d[44]), "=f"(d[45]), "=f"(d[46]), "=f"(d[47]), "=f"(d[48]), "=f"(d[49]), "=f"(d[50]), "=f"(d[51]), "=f"(d[52]), "=f"(d[53]), "=f"(d[54]), "=f"(d[55]), "=f"(d[56]), "=f"(d[57]), "=f"(d[58]), "=f"(d[59]), "=f"(d[60]), "=f"(d[61]), "=f"(d[62]), "=f"(d[63]) : "r"(a0), "r"(a1), "r"(a2), "r"(a3), "l"(db));
}
__device__ __forceinline__ void cw128(float (&d)[64], uint32_t a0, uint32_t a1, uint32_t a2, uint32_t a3, uint64_t db) {
  asm volatile("wgmma.mma_async.sync.aligned.m64n128k16.f32.bf16.bf16 {%0, %1, %2, %3, %4, %5, %6, %7, %8, %9, %10, %11, %12, %13, %14, %15, %16, %17, %18, %19, %20, %21, %22, %23, %24, %25, %26, %27, %28, %29, %30, %31, %32, %33, %34, %35, %36, %37, %38, %39, %40, %41, %42, %43, %44, %45, %46, %47, %48, %49, %50, %51, %52, %53, %54, %55, %56, %57, %58, %59, %60, %61, %62, %63}, {%64,%65,%66,%67}, %68, 1, 1, 1, 0;"
    : "+f"(d[0]), "+f"(d[1]), "+f"(d[2]), "+f"(d[3]), "+f"(d[4]), "+f"(d[5]), "+f"(d[6]), "+f"(d[7]), "+f"(d[8]), "+f"(d[9]), "+f"(d[10]), "+f"(d[11]), "+f"(d[12]), "+f"(d[13]), "+f"(d[14]), "+f"(d[15]), "+f"(d[16]), "+f"(d[17]), "+f"(d[18]), "+f"(d[19]), "+f"(d[20]), "+f"(d[21]), "+f"(d[22]), "+f"(d[23]), "+f"(d[24]), "+f"(d[25]), "+f"(d[26]), "+f"(d[27]), "+f"(d[28]), "+f"(d[29]), "+f"(d[30]), "+f"(d[31]), "+f"(d[32]), "+f"(d[33]), "+f"(d[34]), "+f"(d[35]), "+f"(d[36]), "+f"(d[37]), "+f"(d[38]), "+f"(d[39]), "+f"(d[40]), "+f"(d[41]), "+f"(d[42]), "+f"(d[43]), "+f"(d[44]), "+f"(d[45]), "+f"(d[46]), "+f"(d[47]), "+f"(d[48]), "+f"(d[49]), "+f"(d[50]), "+f"(d[51]), "+f"(d[52]), "+f"(d[53]), "+f"(d[54]), "+f"(d[55]), "+f"(d[56]), "+f"(d[57]), "+f"(d[58]), "+f"(d[59]), "+f"(d[60]), "+f"(d[61]), "+f"(d[62]), "+f"(d[63]) : "r"(a0), "r"(a1), "r"(a2), "r"(a3), "l"(db));
}
__device__ __forceinline__ void cw96(float (&d)[48], uint32_t a0, uint32_t a1, uint32_t a2, uint32_t a3, uint64_t db) {
  asm volatile("wgmma.mma_async.sync.aligned.m64n96k16.f32.bf16.bf16 {%0, %1, %2, %3, %4, %5, %6, %7, %8, %9, %10, %11, %12, %13, %14, %15, %16, %17, %18, %19, %20, %21, %22, %23, %24, %25, %26, %27, %28, %29, %30, %31, %32, %33, %34, %35, %36, %37, %38, %39, %40, %41, %42, %43, %44, %45, %46, %47}, {%48,%49,%50,%51}, %52, 1, 1, 1, 0;"
    : "+f"(d[0]), "+f"(d[1]), "+f"(d[2]), "+f"(d[3]), "+f"(d[4]), "+f"(d[5]), "+f"(d[6]), "+f"(d[7]), "+f"(d[8]), "+f"(d[9]), "+f"(d[10]), "+f"(d[11]), "+f"(d[12]), "+f"(d[13]), "+f"(d[14]), "+f"(d[15]), "+f"(d[16]), "+f"(d[17]), "+f"(d[18]), "+f"(d[19]), "+f"(d[20]), "+f"(d[21]), "+f"(d[22]), "+f"(d[23]), "+f"(d[24]), "+f"(d[25]), "+f"(d[26]), "+f"(d[27]), "+f"(d[28]), "+f"(d[29]), "+f"(d[30]), "+f"(d[31]), "+f"(d[32]), "+f"(d[33]), "+f"(d[34]), "+f"(d[35]), "+f"(d[36]), "+f"(d[37]), "+f"(d[38]), "+f"(d[39]), "+f"(d[40]), "+f"(d[41]), "+f"(d[42]), "+f"(d[43]), "+f"(d[44]), "+f"(d[45]), "+f"(d[46]), "+f"(d[47]) : "r"(a0), "r"(a1), "r"(a2), "r"(a3), "l"(db));
}
__device__ __forceinline__ void cw64(float (&d)[32], uint32_t a0, uint32_t a1, uint32_t a2, uint32_t a3, uint64_t db) {
  asm volatile("wgmma.mma_async.sync.aligned.m64n64k16.f32.bf16.bf16 {%0, %1, %2, %3, %4, %5, %6, %7, %8, %9, %10, %11, %12, %13, %14, %15, %16, %17, %18, %19, %20, %21, %22, %23, %24, %25, %26, %27, %28, %29, %30, %31}, {%32,%33,%34,%35}, %36, 1, 1, 1, 0;"
    : "+f"(d[0]), "+f"(d[1]), "+f"(d[2]), "+f"(d[3]), "+f"(d[4]), "+f"(d[5]), "+f"(d[6]), "+f"(d[7]), "+f"(d[8]), "+f"(d[9]), "+f"(d[10]), "+f"(d[11]), "+f"(d[12]), "+f"(d[13]), "+f"(d[14]), "+f"(d[15]), "+f"(d[16]), "+f"(d[17]), "+f"(d[18]), "+f"(d[19]), "+f"(d[20]), "+f"(d[21]), "+f"(d[22]), "+f"(d[23]), "+f"(d[24]), "+f"(d[25]), "+f"(d[26]), "+f"(d[27]), "+f"(d[28]), "+f"(d[29]), "+f"(d[30]), "+f"(d[31]) : "r"(a0), "r"(a1), "r"(a2), "r"(a3), "l"(db));
}
__device__ __forceinline__ void cw32(float (&d)[16], uint32_t a0, uint32_t a1, uint32_t a2, uint32_t a3, uint64_t db) {
  asm volatile("wgmma.mma_async.sync.aligned.m64n32k16.f32.bf16.bf16 {%0, %1, %2, %3, %4, %5, %6, %7, %8, %9, %10, %11, %12, %13, %14, %15}, {%16,%17,%18,%19}, %20, 1, 1, 1, 0;"
    : "+f"(d[0]), "+f"(d[1]), "+f"(d[2]), "+f"(d[3]), "+f"(d[4]), "+f"(d[5]), "+f"(d[6]), "+f"(d[7]), "+f"(d[8]), "+f"(d[9]), "+f"(d[10]), "+f"(d[11]), "+f"(d[12]), "+f"(d[13]), "+f"(d[14]), "+f"(d[15]) : "r"(a0), "r"(a1), "r"(a2), "r"(a3), "l"(db));
}

struct cpx { float r, i; };
__device__ __forceinline__ cpx cmul(cpx a, cpx b) { return {fmaf(a.r, b.r, -a.i * b.i), fmaf(a.r, b.i, a.i * b.r)}; }
__device__ __forceinline__ cpx csqr(cpx a) { return {fmaf(a.r, a.r, -a.i * a.i), (a.r * a.i) * 2.f}; }
__device__ __forceinline__ cpx cmulc(cpx a, cpx b) { return {fmaf(a.r, b.r, -a.i * b.i), fmaf(-a.r, b.i, -a.i * b.r)}; }
__device__ __forceinline__ cpx cexp_fast(float re, float im) {
  float e;
  asm("ex2.approx.ftz.f32 %0, %1;" : "=f"(e) : "f"(re * 1.4426950408889634f));
  float k = rintf(im * 0.15915494309189535f);
  float r = fmaf(k, -6.2831854820251465f, im);
  r = fmaf(k, 1.7484555314695172e-07f, r);
  float s, c;
  asm("sin.approx.f32 %0, %1;" : "=f"(s) : "f"(r));
  asm("cos.approx.f32 %0, %1;" : "=f"(c) : "f"(r));
  return {e * c, e * s};
}

struct KOps { uint32_t xa[5], xb[5], y[4]; };
__device__ __forceinline__ void kgen_ops(KOps& o, const float4 pr, const float2 qq, const float gf) {
  const cpx C = {pr.z, pr.w};
  const cpx Q = {qq.x, qq.y};
  const cpx V0 = cexp_fast(pr.x * gf, pr.y * gf);
  const cpx V1 = csqr(V0), V2 = csqr(V1), V3 = csqr(V2);
  const cpx Y0 = cmulc(C, V0), Y1 = cmulc(C, V1), Y2 = cmulc(C, V2), Y3 = cmulc(C, V3);
  o.y[0] = pack_f16(Y0.r, Y0.i); o.y[1] = pack_f16(Y1.r, Y1.i); o.y[2] = pack_f16(Y2.r, Y2.i); o.y[3] = pack_f16(Y3.r, Y3.i);
  const cpx Xb = cmul(V3, Q);
  cpx Xc = cmul(Xb, Q), Xd = cmul(Xc, Q);
  o.xa[0] = pack_f16(V3.r, V3.i); o.xb[0] = pack_f16(Xb.r, Xb.i);
  o.xa[1] = pack_f16(Xc.r, Xc.i); o.xb[1] = pack_f16(Xd.r, Xd.i);
#pragma unroll
  for (int k = 2; k < 5; k++) {
    Xc = csqr(Xc); Xd = csqr(Xd);
    o.xa[k] = pack_f16(Xc.r, Xc.i); o.xb[k] = pack_f16(Xd.r, Xd.i);
  }
}
__device__ __forceinline__ void kgen_mma(float (&T)[5][4], const KOps& a, const KOps& b) {
  asm("mma.sync.aligned.m16n8k16.row.col.f32.f16.f16.f32 {%0,%1,%2,%3}, {%20,%21,%22,%23}, {%40,%41}, {%0,%1,%2,%3};\n"
      "mma.sync.aligned.m16n8k16.row.col.f32.f16.f16.f32 {%4,%5,%6,%7}, {%24,%25,%26,%27}, {%40,%41}, {%4,%5,%6,%7};\n"
      "mma.sync.aligned.m16n8k16.row.col.f32.f16.f16.f32 {%8,%9,%10,%11}, {%28,%29,%30,%31}, {%42,%43}, {%8,%9,%10,%11};\n"
      "mma.sync.aligned.m16n8k16.row.col.f32.f16.f16.f32 {%12,%13,%14,%15}, {%32,%33,%34,%35}, {%44,%45}, {%12,%13,%14,%15};\n"
      "mma.sync.aligned.m16n8k16.row.col.f32.f16.f16.f32 {%16,%17,%18,%19}, {%36,%37,%38,%39}, {%46,%47}, {%16,%17,%18,%19};\n"
      : "+f"(T[0][0]), "+f"(T[0][1]), "+f"(T[0][2]), "+f"(T[0][3]), "+f"(T[1][0]), "+f"(T[1][1]), "+f"(T[1][2]), "+f"(T[1][3]),
        "+f"(T[2][0]), "+f"(T[2][1]), "+f"(T[2][2]), "+f"(T[2][3]), "+f"(T[3][0]), "+f"(T[3][1]), "+f"(T[3][2]), "+f"(T[3][3]),
        "+f"(T[4][0]), "+f"(T[4][1]), "+f"(T[4][2]), "+f"(T[4][3])
      : "r"(a.xa[0]), "r"(a.xb[0]), "r"(b.xa[0]), "r"(b.xb[0]), "r"(a.xa[1]), "r"(a.xb[1]), "r"(b.xa[1]), "r"(b.xb[1]),
        "r"(a.xa[2]), "r"(a.xb[2]), "r"(b.xa[2]), "r"(b.xb[2]), "r"(a.xa[3]), "r"(a.xb[3]), "r"(b.xa[3]), "r"(b.xb[3]),
        "r"(a.xa[4]), "r"(a.xb[4]), "r"(b.xa[4]), "r"(b.xb[4]),
        "r"(a.y[0]), "r"(b.y[0]), "r"(a.y[1]), "r"(b.y[1]), "r"(a.y[2]), "r"(b.y[2]), "r"(a.y[3]), "r"(b.y[3]));
}

template <int J0> __device__ __forceinline__ void conv_load4(uint32_t (&f)[4][4], uint32_t ebase, uint32_t zero) {
#pragma unroll
  for (int t = 0; t < 4; t++) {
    f[t][0] = lds32(ebase + (J0 + t) * 128);
    f[t][1] = lds32(ebase + (J0 + t) * 128 + 16);
    f[t][3] = lds32(ebase + (J0 + t) * 128 + 32);
  }
#pragma unroll
  for (int t = 0; t < 4; t++)
    asm volatile("xor.b32 %0, %1, %2;" : "=r"(f[t][2]) : "r"(f[t][1]), "r"(zero));
}
#define CONV_GRP(FN, ACC, J0, F)                                                             \
  wg_fence();                                                                                \
  FN(ACC, F[0][0], F[0][1], F[0][2], F[0][3], de + 4 * (J0));                                \
  FN(ACC, F[1][0], F[1][1], F[1][2], F[1][3], de + 4 * (J0 + 1));                            \
  FN(ACC, F[2][0], F[2][1], F[2][2], F[2][3], de + 4 * (J0 + 2));                            \
  FN(ACC, F[3][0], F[3][1], F[3][2], F[3][3], de + 4 * (J0 + 3));                            \
  wg_commit();
#define CONV_STAGE(ACC, M0)                                                                  \
  _Pragma("unroll") for (int m = (M0); m < (M0) + 4; m++) {                                  \
    *(float2*)(Sw + 8 * m) = make_float2(ACC[4 * m], ACC[4 * m + 1]);                        \
    *(float2*)(Sw + 8 * S_PITCH + 8 * m) = make_float2(ACC[4 * m + 2], ACC[4 * m + 3]);      \
  }
#define CONV_CHANNEL(PRE, MID1, MID2)                                                                    \
  {                                                                                          \
    float a128[64], a96[48], a64[32], a32[16];                                               \
    wg_fence();                                                                              \
    cw128z(a128, fa[0][0], fa[0][1], fa[0][2], fa[0][3], de);                                \
    cw128(a128, fa[1][0], fa[1][1], fa[1][2], fa[1][3], de + 4);                             \
    cw128(a128, fa[2][0], fa[2][1], fa[2][2], fa[2][3], de + 8);                             \
    cw128(a128, fa[3][0], fa[3][1], fa[3][2], fa[3][3], de + 12);                            \
    wg_commit();                                                                             \
    CONV_GRP(cw128, a128, 4, fb)                                                             \
    MID1                                                                                     \
    wg_wait<1>(); conv_load4<8>(fa, ebase, zero);                                            \
    wg_wait<0>(); conv_load4<12>(fb, ebase, zero);                                           \
    _Pragma("unroll") for (int i = 0; i < 48; i++) movf(a96[i], a128[i]);                       \
    CONV_GRP(cw96, a96, 8, fa)                                                               \
    CONV_GRP(cw96, a96, 12, fb)                                                              \
    MID2                                                                                     \
    PRE                                                                                      \
    CONV_STAGE(a128, 12)                                                                     \
    wg_wait<1>(); conv_load4<16>(fa, ebase, zero);                                           \
    wg_wait<0>(); conv_load4<20>(fb, ebase, zero);                                           \
    _Pragma("unroll") for (int i = 0; i < 32; i++) movf(a64[i], a96[i]);                        \
    CONV_GRP(cw64, a64, 16, fa)                                                              \
    CONV_GRP(cw64, a64, 20, fb)                                                              \
    CONV_STAGE(a96, 8)                                                                       \
    wg_wait<1>(); conv_load4<24>(fa, ebase, zero);                                           \
    wg_wait<0>(); conv_load4<28>(fb, ebase, zero);                                           \
    _Pragma("unroll") for (int i = 0; i < 16; i++) movf(a32[i], a64[i]);                        \
    CONV_GRP(cw32, a32, 24, fa)                                                              \
    CONV_GRP(cw32, a32, 28, fb)                                                              \
    CONV_STAGE(a64, 4)                                                                       \
    load_u(ch);                                                                              \
    wg_wait<0>();                                                                            \
    CONV_STAGE(a32, 0)                                                                       \
  }

__device__ __forceinline__ int part_slot(int s, int v) {
  if (s == 6) return CV_E + 2 * v * E_CH;
  if (s == 5) return v ? (SM_PR - SM_X) : (CV_S + 2 * S_WG);
  return CV_S + v * S_WG + (s & 3) * 8192;
}
template <int V> struct IC { static constexpr int value = V; };

struct Params {
  const __nv_bfloat16* x;
  const __nv_bfloat16* log_A_real;
  const __nv_bfloat16* A_imag;
  const __nv_bfloat16* C_real;
  const __nv_bfloat16* C_imag;
  const __nv_bfloat16* log_dt;
  const __nv_bfloat16* D_skip;
  const __nv_bfloat16* gate_w;
  const __nv_bfloat16* w_gate;
  const __nv_bfloat16* w_up;
  const __nv_bfloat16* w_down;
  __nv_bfloat16* out;
};

struct Maps {
  CUtensorMap X, Wg, Wu, Wg3[2], Wu3[2], Wd, AT;
};

__device__ __forceinline__ uint32_t ld_epoch() { return *(volatile uint32_t*)&g_epoch; }
__device__ __forceinline__ uint32_t dup_lo(uint32_t w) { return __byte_perm(w, w, 0x1010); }
__device__ __forceinline__ uint32_t dup_hi(uint32_t w) { return __byte_perm(w, w, 0x3232); }

__global__ void __launch_bounds__(NTHREADS, 1)
fused_kernel(const __grid_constant__ Maps M, const Params P) {
  extern __shared__ __align__(1024) uint8_t smem[];
  const uint32_t sb = smem_u32(smem);
  const uint32_t bars = sb + SM_BAR;
  const int tid = threadIdx.x;
  const int warp = __shfl_sync(0xffffffffu, tid >> 5, 0), lane = tid & 31;
  const int b = blockIdx.x;
  const int cl = b >> 1;
  const int jf = cl & 7;
  const int it_ = ((cl >> 3) << 1) | (b & 1);
  const int d0 = b * 4;

  const int kch = warp / 3, kpart = warp - 3 * kch;
  const int kk0 = kpart == 0 ? 0 : (kpart == 1 ? 6 : 11), nks = kpart == 0 ? 6 : 5;
  uint32_t pw0[2], pw1[2], pldt;
  {
    unsigned short raw[9];
    int n0 = 8 * kk0 + lane, n1 = n0 + 32;
    n0 = (d0 + kch) * NS_ + n0;
    n1 = (d0 + kch) * NS_ + (n1 < NS_ ? n1 : NS_ - 1);
    asm volatile("ld.global.nc.u16 %0, [%9];\n\tld.global.nc.u16 %1, [%10];\n\tld.global.nc.u16 %2, [%11];\n\t"
                 "ld.global.nc.u16 %3, [%12];\n\tld.global.nc.u16 %4, [%13];\n\tld.global.nc.u16 %5, [%14];\n\t"
                 "ld.global.nc.u16 %6, [%15];\n\tld.global.nc.u16 %7, [%16];\n\tld.global.nc.u16 %8, [%17];"
                 : "=h"(raw[0]), "=h"(raw[1]), "=h"(raw[2]), "=h"(raw[3]), "=h"(raw[4]), "=h"(raw[5]), "=h"(raw[6]), "=h"(raw[7]), "=h"(raw[8])
                 : "l"(P.log_A_real + n0), "l"(P.A_imag + n0), "l"(P.C_real + n0), "l"(P.C_imag + n0),
                   "l"(P.log_A_real + n1), "l"(P.A_imag + n1), "l"(P.C_real + n1), "l"(P.C_imag + n1), "l"(P.log_dt + d0 + kch));
  if (lane == 0) {
    if (warp == 8) {
      mbar_init(bars + 8 * (B_FULL + 0), 1); mbar_init(bars + 8 * (B_FULL + 2), 1); mbar_init(bars + 8 * (B_FULL + 4), 1);
      mbar_init(bars + 8 * (B_XFULL + 0), 1); mbar_init(bars + 8 * (B_XFULL + 2), 1); mbar_init(bars + 8 * (B_XFULL + 4), 1);
    } else if (warp == 9) {
      mbar_init(bars + 8 * (B_FULL + 1), 1); mbar_init(bars + 8 * (B_FULL + 3), 1);
      mbar_init(bars + 8 * (B_XFULL + 1), 1); mbar_init(bars + 8 * (B_XFULL + 3), 1); mbar_init(bars + 8 * (B_XFULL + 5), 1);
    } else {
      const int wi = warp < 8 ? warp : warp - 2;
#pragma unroll
      for (int r = 0; r < 5; r++) {
        int i = wi + 10 * r + 5;
        if (i >= B_XFULL) i += 6;
        uint32_t cnt = 1;
        if ((i >= B_EMPTY && i < B_EMPTY + 5) || (i >= B_XFREE && i < B_XFREE + 8) || (i >= B_SENT && i < B_SENT + 8) || i == B_ADONE) cnt = 8;
        if (i == B_RRDY || i == B_KSUM) cnt = 2;
        if (i == B_GOT) cnt = 7;
        mbar_init(bars + 8 * i, cnt);
      }
    }
    asm volatile("fence.mbarrier_init.release.cluster;" ::: "memory");
  }
  __syncwarp();
    pw0[0] = (uint32_t)raw[0] | ((uint32_t)raw[1] << 16); pw1[0] = (uint32_t)raw[2] | ((uint32_t)raw[3] << 16);
    pw0[1] = (uint32_t)raw[4] | ((uint32_t)raw[5] << 16); pw1[1] = (uint32_t)raw[6] | ((uint32_t)raw[7] << 16);
    pldt = raw[8];
  }
  TM_IF(tid == 0, 21);

  auto issue_stage = [&](int s, int slot) {
    const uint32_t dst = sb + SM_RING + slot * 16384;
    const uint32_t fb = bars + 8 * (B_FULL + slot);
    if (s < 32) {
      const int f0 = jf * 224 + ((s >> 4) << 7);
      const int k0 = (s & 15) * 32;
      mbar_expect(fb, 16384);
      if (jf == 7 && s >= 16) {
        tma2d(dst, &M.Wg, f0, k0, fb);
        tma2d(dst + 4096, &M.Wg, f0 + 64, k0, fb);
        tma2d(dst + 8192, &M.Wu, f0, k0, fb);
        tma2d(dst + 12288, &M.Wu, f0 + 64, k0, fb);
      } else {
        tma3d(dst, &M.Wg3[jf & 1], 0, k0, f0 >> 6, fb);
        tma3d(dst + 8192, &M.Wu3[jf & 1], 0, k0, f0 >> 6, fb);
      }
    } else {
      const int s2 = s - 32;
      const int p = (jf + 1 + (s2 >> 1)) & 7;
      mbar_expect(fb, 14336);
      tma2d(dst, &M.Wd, p * 64, jf * 224 + (s2 & 1) * 112, fb);
    }
  };
  auto issue_x = [&](int kb) {
    mbar_expect(bars + 8 * (B_XFULL + kb), 16384);
    tma2d(sb + SM_X + kb * 16384, &M.X, kb * 64, it_ * 128, bars + 8 * (B_XFULL + kb));
  };
  {
    const int g = lane >> 2, q = lane & 3;
    const float dtf = bf16r(expf(bf_lo(pldt)));
    const int pro = kch * 128 + 8 * kk0;
    float4* prm = (float4*)(smem + SM_PR) + pro;
    float2* prq = (float2*)(smem + SM_PR + 512 * 16) + pro;
    const bool valid1 = lane + 32 < 8 * nks;
    float m0 = fmaxf(fmaxf(fabsf(bf_lo(pw1[0])), fabsf(bf_hi(pw1[0]))), fmaxf(fabsf(bf_lo(pw1[1])), fabsf(bf_hi(pw1[1])))) * dtf;
#pragma unroll
    for (int o = 16; o > 0; o >>= 1) m0 = fmaxf(m0, __shfl_xor_sync(0xffffffffu, m0, o));
    TM_IF(tid == 0 && m0 >= 0.f, 0);
    if (m0 >= 0.f || m0 != m0) {
      if (tid == 256) {
        issue_x(0); issue_stage(0, 0); issue_stage(2, 2); issue_x(2); issue_stage(4, 4); issue_x(4);
      } else if (tid == 288) {
        issue_stage(1, 1); issue_x(1); issue_stage(3, 3); issue_x(3); issue_x(5);
      }
    }
    __syncwarp();
    const uint32_t e0 = min(max(__float_as_uint(m0) >> 23, 1u), 253u);
    const float sc = __uint_as_float((254u - e0) << 23);
    const float us = 2.f * __uint_as_float(e0 << 23);
    float pe = 0.f;
#pragma unroll
    for (int r = 0; r < 2; r++) {
      float4 v;
      v.x = -bf16r(expf(bf_lo(pw0[r]))) * dtf;
      v.y = bf_hi(pw0[r]) * dtf;
      v.z = bf_lo(pw1[r]) * dtf * sc;
      v.w = bf_hi(pw1[r]) * dtf * sc;
      const cpx Q = cexp_fast(v.x * 64.f, v.y * 64.f);
      const cpx We = cexp_fast(v.x * 2048.f, v.y * 2048.f);
      if (r == 0 || valid1) {
        pe += v.z * We.r - v.w * We.i;
        prm[lane + 32 * r] = v;
        prq[lane + 32 * r] = make_float2(Q.r, Q.i);
      }
    }
#pragma unroll
    for (int o = 16; o > 0; o >>= 1) pe += __shfl_xor_sync(0xffffffffu, pe, o);
    __syncwarp();
    TM_IF(tid == 0, 1);
    float T[5][4];
#pragma unroll
    for (int i = 0; i < 20; i++) T[i >> 2][i & 3] = 0.f;
    const float gf = (float)g;
#pragma unroll 1
    for (int ks = 0; ks < nks; ks++) {
      KOps o1, o2;
      kgen_ops(o1, prm[8 * ks + q], prq[8 * ks + q], gf);
      kgen_ops(o2, prm[8 * ks + 4 + q], prq[8 * ks + 4 + q], gf);
      kgen_mma(T, o1, o2);
    }
    float* kp = (float*)(smem + SM_X + 6 * 16384) + warp * KC_STRIDE + 8 * g + 2 * q;
#pragma unroll
    for (int k = 0; k < 5; k++) {
      *(float2*)(kp + 128 * k) = make_float2(T[k][0] * us, T[k][1] * us);
      *(float2*)(kp + 128 * k + 64) = make_float2(T[k][2] * us, T[k][3] * us);
    }
    if (lane == 0) { kp[640] = pe * us; kp[641] = 0.f; }
    TM_IF(tid == 0, 2);
  }
  __syncthreads();

  if (warp >= 8) {
    asm volatile("setmaxnreg.dec.sync.aligned.u32 104;");
    if (warp < 10) {
      if (lane == 0) {
        int slot = (warp == 8) ? 1 : 0;
        uint32_t ph = 0;
#pragma unroll 1
        for (int s = (warp == 8) ? 6 : 5; s < 48; s += 2) {
          if (s == 10) { mbar_wait(bars + 8 * B_KSUM, 0); issue_x(6); issue_x(7); }
          mbar_wait(bars + 8 * (B_EMPTY + slot), ph);
          issue_stage(s, slot);
          slot += 2;
          if (slot >= 5) { slot -= 5; ph ^= 1; }
        }
      }
      __syncwarp();
      {
        const uint4 gw0 = *(const uint4*)(P.gate_w + lane * 16);
        const uint4 gw1 = *(const uint4*)(P.gate_w + lane * 16 + 8);
        uint4 xa[8], xb[8];
#pragma unroll
        for (int i = 0; i < 8; i++) {
          xa[i] = *(const uint4*)(P.x + (b * 16 + (warp - 8) * 8 + i) * D_ + lane * 16);
          xb[i] = *(const uint4*)(P.x + (b * 16 + (warp - 8) * 8 + i) * D_ + lane * 16 + 8);
        }
        float sg[8];
#pragma unroll
        for (int i = 0; i < 8; i++) {
          const uint32_t pr[8] = {hmul2_bf16(xa[i].x, gw0.x), hmul2_bf16(xa[i].y, gw0.y), hmul2_bf16(xa[i].z, gw0.z), hmul2_bf16(xa[i].w, gw0.w),
                                  hmul2_bf16(xb[i].x, gw1.x), hmul2_bf16(xb[i].y, gw1.y), hmul2_bf16(xb[i].z, gw1.z), hmul2_bf16(xb[i].w, gw1.w)};
          float s = 0.f;
#pragma unroll
          for (int k = 0; k < 8; k++) s += bf_lo(pr[k]) + bf_hi(pr[k]);
          sg[i] = s;
        }
#pragma unroll
        for (int o = 16; o > 0; o >>= 1) {
#pragma unroll
          for (int i = 0; i < 8; i++) sg[i] += __shfl_xor_sync(0xffffffffu, sg[i], o);
        }
        float z = sg[0];
#pragma unroll
        for (int i = 1; i < 8; i++) z = (lane == i) ? sg[i] : z;
        if (lane < 8) g_gate[b * 16 + (warp - 8) * 8 + lane] = bf16r(1.f / (1.f + expf(-bf16r(z))));
      }
      bar_sync(3, 64);
      if (tid == 288) asm volatile("red.release.gpu.global.add.u32 [%0], 1;" ::"l"(&g_done1) : "memory");
      TM_IF(tid == 256, 16);
      if (warp == 8) {
        if (lane >= 1 && lane < 8) {
          const uint32_t tag = ld_epoch() + 1;
          const uint32_t* fp = g_flag + ((it_ * 8 + jf) * 8 + ((jf - lane) & 7));
          int itc = 0;
          while (ld_acquire(fp) != tag) { __nanosleep(100); if (++itc > SPIN_LIMIT) FAIL(-2, lane); }
          mbar_arrive(bars + 8 * B_GOT);
          TM_IF(lane == 7, 25);
        }
      } else if (lane == 0) {
        const uint32_t tag = ld_epoch() + 1;
#pragma unroll 1
        for (int rnd = 0; rnd < 2; rnd++) {
          if (rnd == 1) {
            int itc = 0;
            while ((int)(ld_acquire(&g_done1) - (uint32_t)NCTA * tag) < 0) { if (++itc > SPIN_LIMIT) FAIL(-1, 0); }
            mbar_wait(bars + 8 * B_ADONE, 1);
          } else {
            mbar_wait_lazy<100>(bars + 8 * B_ADONE, 0);
          }
          TM_IF(true, 24);
#pragma unroll
          for (int v = 0; v < 2; v++)
            asm volatile("cp.async.bulk.global.shared::cta.bulk_group [%0], [%1], %2;"
                         ::"l"(g_aT + (d0 + 2 * v + rnd) * L_), "r"(sb + SM_X + CV_R + (2 * v + rnd) * R_CH), "r"(4096) : "memory");
          asm volatile("cp.async.bulk.commit_group;" ::: "memory");
          asm volatile("cp.async.bulk.wait_group 0;" ::: "memory");
          asm volatile("red.relaxed.gpu.global.add.u32 [%0], 1;" ::"l"(g_cnt + 32 * (b >> 4)) : "memory");
        }
        TM_IF(true, 26);
        {
          int itc = 0;
          while ((int)(ld_acquire(g_cnt + 32 * jf) - 32u * tag) < 0) { if (++itc > SPIN_LIMIT) FAIL(-3, 0); }
        }
        TM_IF(true, 23);
        asm volatile("fence.proxy.async.global;" ::: "memory");
        mbar_expect(bars + 8 * B_ATILE, 16384);
        tma2d(sb + SM_AT, &M.AT, it_ * 128, jf * 64, bars + 8 * B_ATILE);
        tma2d(sb + SM_AT + 8192, &M.AT, it_ * 128 + 64, jf * 64, bars + 8 * B_ATILE);
      }
      __syncwarp();
    } else {
      const int w = warp - 10;
      const int wt = tid - 320;
      {
        const float2* kp = (const float2*)(smem + SM_X + 6 * 16384);
        uint32_t* kb = (uint32_t*)(smem + SM_KB);
#pragma unroll
        for (int ch = 0; ch < 4; ch++) {
#pragma unroll
          for (int i = 0; i < 6; i++) {
            const int o = wt + 64 * i;
            if (i < 5 || o < 321) {
              const float2 a0 = kp[(3 * ch) * (KC_STRIDE / 2) + o], a1 = kp[(3 * ch + 1) * (KC_STRIDE / 2) + o], a2 = kp[(3 * ch + 2) * (KC_STRIDE / 2) + o];
              kb[ch * (KC_STRIDE / 2) + o] = pack_bf16(a0.x + a1.x + a2.x, a0.y + a1.y + a2.y);
            }
          }
        }
      }
      fence_async();
      bar_sync(1, 64);
      if (lane == 0) mbar_arrive(bars + 8 * B_KSUM);
      {
        const uint32_t zz = *(volatile uint32_t*)&g_zero;
        uint2 ur[4][8];
#pragma unroll
        for (int i = 0; i < 4; i++) {
#pragma unroll
          for (int r = 0; r < 8; r++) {
            uint32_t ck;
            asm volatile("nanosleep.u32 120;\n\tmov.u32 %0, %%clock;" : "=r"(ck) :: "memory");
            asm volatile("ld.global.nc.v2.u32 {%0,%1}, [%2];" : "=r"(ur[i][r].x), "=r"(ur[i][r].y)
                         : "l"(P.x + ((wt + 64 * i) * 8 + r) * D_ + d0 + (ck & zz)));
          }
        }
        mbar_wait_lazy<200>(bars + 8 * (B_XFREE + 7), 0);
        TM_IF(wt == 0, 18);
#pragma unroll
        for (int i = 0; i < 4; i++) {
          const int item = wt + 64 * i;
          const int c = item >> 1, hh = item & 1;
#pragma unroll
          for (int ch = 0; ch < 4; ch++) {
            uint32_t v[4];
#pragma unroll
            for (int k = 0; k < 4; k++) {
              const uint32_t lo = (ch < 2) ? ur[i][7 - 2 * k].x : ur[i][7 - 2 * k].y;
              const uint32_t hi = (ch < 2) ? ur[i][6 - 2 * k].x : ur[i][6 - 2 * k].y;
              v[k] = (ch & 1) ? __byte_perm(lo, hi, 0x7632) : __byte_perm(lo, hi, 0x5410);
            }
            *(uint4*)(smem + SM_X + CV_R + ch * R_CH + (1 - hh) * R_HALF + (127 - c) * 16) = make_uint4(v[0], v[1], v[2], v[3]);
          }
        }
        if (lane < 28) {
#pragma unroll
          for (int z = 0; z < 4; z++)
            *(uint4*)(smem + SM_X + CV_R + (4 * w + z) * R_HALF + (128 + lane) * 16) = make_uint4(0, 0, 0, 0);
        }
      }
      auto part_store = [&](int s) {
        mbar_wait_lazy<100>(bars + 8 * (B_SENT + s), 0);
        const int fi = (it_ * 8 + ((jf + 1 + s) & 7)) * 8 + jf;
#pragma unroll
        for (int v = 0; v < 2; v++)
          asm volatile("cp.async.bulk.global.shared::cta.bulk_group [%0], [%1], %2;"
                       ::"l"(g_part + (size_t)fi * 1024 + v * 512), "r"(sb + SM_X + part_slot(s, v)), "r"(8192) : "memory");
        asm volatile("cp.async.bulk.commit_group;" ::: "memory");
      };
      if (w == 0 && lane == 0) part_store(0);
      __syncwarp();
      {
#pragma unroll 1
      for (int G = w; G < 8; G += 2) {
        const int n = 32 * G + lane;
        uint4 c0[4], c1[4];
        if (G >= 4) {
#pragma unroll
          for (int ch = 0; ch < 4; ch++) {
            const uint8_t* kc = smem + SM_KB + ch * KC_STRIDE * 2;
            const uint32_t a = *(const unsigned short*)(kc + (384 + n) * 2), bb = *(const unsigned short*)(kc + (385 + n) * 2);
            const uint32_t aa = a | (a << 16), b2 = bb | (bb << 16);
            const uint32_t tie = (n & 1) ? bb : a;
            c0[ch] = make_uint4(aa, a | (tie << 16), b2, b2);
            c1[ch] = make_uint4(aa, tie | (bb << 16), b2, b2);
          }
        } else if (G >= 2) {
#pragma unroll
          for (int ch = 0; ch < 4; ch++) {
            const uint8_t* kc = smem + SM_KB + ch * KC_STRIDE * 2;
            const uint32_t w0 = *(const uint32_t*)(kc + (256 + 2 * n) * 2), w1 = *(const uint32_t*)(kc + (258 + 2 * n) * 2);
            c0[ch] = make_uint4(dup_lo(w0), dup_hi(w0), __byte_perm(w0, w1, 0x5432), dup_lo(w1));
            c1[ch] = make_uint4(w0, dup_hi(w0), dup_lo(w1), dup_lo(w1));
          }
        } else if (G == 1) {
#pragma unroll
          for (int ch = 0; ch < 4; ch++) {
            const uint8_t* kc = smem + SM_KB + ch * KC_STRIDE * 2;
            const uint2 w01 = *(const uint2*)(kc + (128 + 4 * n) * 2);
            const uint32_t w2 = *(const uint32_t*)(kc + (132 + 4 * n) * 2);
            c0[ch] = make_uint4(w01.x, dup_lo(w01.y), w01.y, dup_lo(w2));
            c1[ch] = make_uint4(__byte_perm(w01.x, w01.y, 0x5432), dup_lo(w01.y), __byte_perm(w01.y, w2, 0x5432), dup_lo(w2));
          }
        } else {
#pragma unroll
          for (int ch = 0; ch < 4; ch++) {
            const uint8_t* kc = smem + SM_KB + ch * KC_STRIDE * 2;
            const uint4 wv = *(const uint4*)(kc + (8 * n) * 2);
            const uint32_t w4 = *(const uint32_t*)(kc + (8 * n + 8) * 2);
            c0[ch] = make_uint4(__byte_perm(wv.x, wv.y, 0x5432), __byte_perm(wv.y, wv.z, 0x5432), __byte_perm(wv.z, wv.w, 0x5432), __byte_perm(wv.w, w4, 0x5432));
            c1[ch] = make_uint4(wv.y, wv.z, wv.w, (n == 31) ? dup_lo(w4) : w4);
          }
          if (lane < 8) {
            const int ch = lane >> 1, hi = lane & 1;
            const uint32_t k01 = *(const uint32_t*)(smem + SM_KB + ch * KC_STRIDE * 2);
            uint8_t* e = smem + SM_X + CV_E + ch * E_CH + hi * 16;
            *(uint4*)e = make_uint4(0, 0, 0, hi ? (k01 << 16) : 0u);
            *(uint4*)(e + E_COPY) = make_uint4(0, 0, 0, hi ? k01 : 0u);
          }
        }
#pragma unroll
        for (int ch = 0; ch < 4; ch++) {
          uint8_t* e = smem + SM_X + CV_E + ch * E_CH + (n + 2) * 16;
          *(uint4*)e = c0[ch];
          *(uint4*)(e + E_COPY) = c1[ch];
        }
      }
        fence_async();
        __syncwarp();
        if (lane == 0) mbar_arrive(bars + 8 * B_RRDY);
        TM_IF(wt == 0, 19);
      }
      if (lane == 0) {
        const uint32_t tag = ld_epoch() + 1;
        auto publish = [&](int s) {
          asm volatile("st.relaxed.gpu.global.u32 [%0], %1;" ::"l"(g_flag + ((it_ * 8 + ((jf + 1 + s) & 7)) * 8 + jf)), "r"(tag) : "memory");
          TM_IF(true, 3 + s);
        };
#pragma unroll 1
        for (int s = w; s < 7; s += 2) {
          if (s > 0) part_store(s);
          asm volatile("cp.async.bulk.wait_group.read 0;" ::: "memory");
          mbar_arrive(bars + 8 * (B_STF + s));
          if (s >= 2 && s < 6) {
            asm volatile("cp.async.bulk.wait_group 1;" ::: "memory");
            publish(s - 2);
          }
          if (s >= 4) {
            asm volatile("cp.async.bulk.wait_group 0;" ::: "memory");
            publish(s);
          }
        }
      }
      __syncwarp();
    }
    bar_sync(2, 128);
    if (tid == 256) {
      const uint32_t tk = atomicAdd(&g_exit, 1u);
      if (tk == NCTA - 1) {
        g_exit = 0;
        *(volatile uint32_t*)&g_epoch = ld_epoch() + 1;
      }
    }
    TM_IF(tid == 256, 13);
  } else {
    asm volatile("setmaxnreg.inc.sync.aligned.u32 200;");
    const int wg = warp >> 2;
    const int g = lane >> 2, q = lane & 3;
    const uint32_t dsk = *(const uint32_t*)(P.D_skip + d0 + 2 * wg);
    uint32_t hf[56];
    {
      float acc[128];
#pragma unroll
      for (int i = 0; i < 128; i++) zero_reg(acc[i]);
#pragma unroll 1
      for (int st = 0; st < 16; st++) {
        const int slot = st % 5;
        if ((st & 1) == 0) mbar_wait(bars + 8 * (B_XFULL + (st >> 1)), 0);
        mbar_wait(bars + 8 * (B_FULL + slot), (st / 5) & 1);
        const uint64_t da = mkdesc(sb + SM_X + (st >> 1) * 16384 + wg * 8192 + (st & 1) * 64, 16, 1024, 1);
        const uint64_t db = mkdesc(sb + SM_RING + slot * 16384, 4096, 1024, 1);
        wg_fence();
        wgmma_ss_n256(acc, da, db);
        wgmma_ss_n256(acc, da + 2, db + 128);
        wg_commit();
        if (st > 0) {
          wg_wait<1>();
          if (lane == 0) mbar_arrive(bars + 8 * (B_EMPTY + (st - 1) % 5));
        }
      }
      wg_wait<0>();
      if (lane == 0) mbar_arrive(bars + 8 * (B_EMPTY + 15 % 5));
#pragma unroll
      for (int m = 0; m < 16; m++) {
        hf[2 * m] = hmul2_bf16(pack_bf16(acc[4 * m], acc[4 * m + 1]), pack_bf16(acc[64 + 4 * m], acc[64 + 4 * m + 1]));
        hf[2 * m + 1] = hmul2_bf16(pack_bf16(acc[4 * m + 2], acc[4 * m + 3]), pack_bf16(acc[64 + 4 * m + 2], acc[64 + 4 * m + 3]));
      }
    }
    float accA[32], accB[32];
    auto issue_half = [&](float (&acc)[32], int s, auto half_tag) {
      constexpr int half = decltype(half_tag)::value;
      if (half == 0) {
#pragma unroll
        for (int i = 0; i < 32; i++) zero_reg(acc[i]);
      }
      const int st = 32 + 2 * s + half;
      const int slot = st % 5;
      mbar_wait(bars + 8 * (B_FULL + slot), (st / 5) & 1);
      uint32_t sbase;
      asm volatile("mov.b32 %0, %1;" : "=r"(sbase) : "r"(sb + SM_RING + slot * 16384));
      const uint64_t db = mkdesc(sbase, 1024, 1024, 1);
      wg_fence();
#pragma unroll
      for (int k = 0; k < 7; k++) {
        const int ks = 7 * half + k;
        wgmma_rs_n64t(acc, hf[4 * ks], hf[4 * ks + 1], hf[4 * ks + 2], hf[4 * ks + 3], db + k * 128);
      }
      wg_commit();
    };
    auto release = [&](int st) { if (lane == 0) mbar_arrive(bars + 8 * (B_EMPTY + st % 5)); };
    using H0 = IC<0>;
    using H1 = IC<1>;
    {
      float accg[48], accu[48];
#pragma unroll
      for (int i = 0; i < 48; i++) { zero_reg(accg[i]); zero_reg(accu[i]); }
      const uint32_t xrow = sb + SM_X + (wg * 64 + (warp & 3) * 16 + (lane & 15)) * 128;
      const uint32_t xsw = lane & 7, xhi = lane >> 4;
      uint32_t a0[4], a1[4], a2[4], a3[4];
#pragma unroll 1
      for (int kb = 0; kb < 8; kb++) {
        const uint32_t xb = xrow + kb * 16384;
        {
          const int st = 16 + 2 * kb, slot = st % 5;
          ldsm4(a0, xb + (((0 + xhi) ^ xsw) << 4));
          ldsm4(a1, xb + (((2 + xhi) ^ xsw) << 4));
          mbar_wait(bars + 8 * (B_FULL + slot), (st / 5) & 1);
          const uint64_t db = mkdesc(sb + SM_RING + slot * 16384, 4096, 1024, 1);
          wg_fence();
          wgmma_rs_n96(accg, a0[0], a0[1], a0[2], a0[3], db);
          wgmma_rs_n96(accu, a0[0], a0[1], a0[2], a0[3], db + 512);
          wgmma_rs_n96(accg, a1[0], a1[1], a1[2], a1[3], db + 128);
          wgmma_rs_n96(accu, a1[0], a1[1], a1[2], a1[3], db + 128 + 512);
          wg_commit();
          wg_wait<1>();
          if (kb > 0 && lane == 0) mbar_arrive(bars + 8 * (B_EMPTY + (st - 1) % 5));
        }
        {
          const int st = 17 + 2 * kb, slot = st % 5;
          ldsm4(a2, xb + (((4 + xhi) ^ xsw) << 4));
          ldsm4(a3, xb + (((6 + xhi) ^ xsw) << 4));
          mbar_wait(bars + 8 * (B_FULL + slot), (st / 5) & 1);
          const uint64_t db = mkdesc(sb + SM_RING + slot * 16384, 4096, 1024, 1);
          wg_fence();
          wgmma_rs_n96(accg, a2[0], a2[1], a2[2], a2[3], db);
          wgmma_rs_n96(accu, a2[0], a2[1], a2[2], a2[3], db + 512);
          wgmma_rs_n96(accg, a3[0], a3[1], a3[2], a3[3], db + 128);
          wgmma_rs_n96(accu, a3[0], a3[1], a3[2], a3[3], db + 128 + 512);
          wg_commit();
          wg_wait<1>();
          if (lane == 0) mbar_arrive(bars + 8 * (B_EMPTY + (st - 1) % 5));
        }
      }
      issue_half(accA, 0, H0{});
      wg_wait<1>();
      if (lane == 0) { mbar_arrive(bars + 8 * (B_EMPTY + 31 % 5)); mbar_arrive(bars + 8 * (B_XFREE + 7)); }
#pragma unroll
      for (int m = 0; m < 12; m++) {
        hf[32 + 2 * m] = hmul2_bf16(pack_bf16(accg[4 * m], accg[4 * m + 1]), pack_bf16(accu[4 * m], accu[4 * m + 1]));
        hf[32 + 2 * m + 1] = hmul2_bf16(pack_bf16(accg[4 * m + 2], accg[4 * m + 3]), pack_bf16(accu[4 * m + 2], accu[4 * m + 3]));
      }
    }
    auto send_pass = [&](float (&acc)[32], int s) {
      uint4* dst = (uint4*)(smem + SM_X + part_slot(s, wg) + (warp & 3) * 2048) + lane;
#pragma unroll
      for (int c = 0; c < 4; c++) {
        uint4 v;
        v.x = pack_bf16(acc[8 * c], acc[8 * c + 1]); v.y = pack_bf16(acc[8 * c + 2], acc[8 * c + 3]);
        v.z = pack_bf16(acc[8 * c + 4], acc[8 * c + 5]); v.w = pack_bf16(acc[8 * c + 6], acc[8 * c + 7]);
        dst[c * 32] = v;
      }
      fence_async();
      __syncwarp();
      if (lane == 0) mbar_arrive(bars + 8 * (B_SENT + s));
    };
    auto part_load = [&](uint4 (&v)[4], int k) {
      const uint4* sp = g_part + (size_t)(((it_ * 8 + jf) * 8 + ((jf - k) & 7)) * 8 + warp) * 128 + lane;
#pragma unroll
      for (int c = 0; c < 4; c++) v[c] = ld_cg4(sp + c * 32);
    };
    auto part_add = [&](const uint4 (&v)[4]) {
#pragma unroll
      for (int c = 0; c < 4; c++) {
        accA[8 * c] += bf_lo(v[c].x); accA[8 * c + 1] += bf_hi(v[c].x); accA[8 * c + 2] += bf_lo(v[c].y); accA[8 * c + 3] += bf_hi(v[c].y);
        accA[8 * c + 4] += bf_lo(v[c].z); accA[8 * c + 5] += bf_hi(v[c].z); accA[8 * c + 6] += bf_lo(v[c].w); accA[8 * c + 7] += bf_hi(v[c].w);
      }
    };
    issue_half(accA, 0, H1{}); wg_wait<1>(); release(32);
    mbar_wait(bars + 8 * (B_XFREE + 7), 0);
    issue_half(accB, 1, H0{}); wg_wait<1>(); release(33); send_pass(accA, 0);
    issue_half(accB, 1, H1{}); wg_wait<1>(); release(34);
    issue_half(accA, 2, H0{}); wg_wait<1>(); release(35); send_pass(accB, 1);
    issue_half(accA, 2, H1{}); wg_wait<1>(); release(36);
    issue_half(accB, 3, H0{}); wg_wait<1>(); release(37); send_pass(accA, 2);
    issue_half(accB, 3, H1{}); wg_wait<1>(); release(38);
    issue_half(accA, 4, H0{}); wg_wait<1>(); release(39); send_pass(accB, 3);
    issue_half(accA, 4, H1{}); wg_wait<1>(); release(40);
    issue_half(accB, 5, H0{}); wg_wait<1>(); release(41); mbar_wait(bars + 8 * (B_STF + 0), 0); send_pass(accA, 4);
    issue_half(accB, 5, H1{}); wg_wait<1>(); release(42);
    wg_wait<0>(); send_pass(accB, 5);
    {
      TM_IF(tid == 0, 10);
      const int w = warp & 3;
      mbar_wait(bars + 8 * B_RRDY, 0);
      TM_IF(tid == 0, 11);
      const uint32_t zero = lds32(sb + SM_X + CV_R + (2 * wg + 1) * R_CH + 128 * 16);
      const int c = tid & 127;
      const float* Sr = (const float*)(smem + SM_X + CV_S + wg * S_WG) + (127 - c);
      float* Sw = (float*)(smem + SM_X + CV_S + wg * S_WG) + w * 16 * S_PITCH + g * S_PITCH + 2 * q;
      uint32_t fa[4][4], fb[4][4];
      uint32_t ares[8] = {0, 0, 0, 0, 0, 0, 0, 0}, rv[8];
      auto load_u = [&](int ch) {
        const uint4 r0v = *(const uint4*)(smem + SM_X + CV_R + ch * R_CH + (127 - c) * 16);
        const uint4 r1v = *(const uint4*)(smem + SM_X + CV_R + ch * R_CH + R_HALF + (127 - c) * 16);
        rv[0] = r0v.x; rv[1] = r0v.y; rv[2] = r0v.z; rv[3] = r0v.w; rv[4] = r1v.x; rv[5] = r1v.y; rv[6] = r1v.z; rv[7] = r1v.w;
      };
#define POST(r2, dk2)                                                                              \
      {                                                                                            \
        float y_[2];                                                                               \
        _Pragma("unroll") for (int t2 = 0; t2 < 2; t2++) {                                         \
          const int r0 = 2 * (r2) + t2;                                                            \
          const float s1 = c >= 1 ? Sr[(16 + r0) * S_PITCH + 1] : 0.f;                             \
          const float s2 = c >= 2 ? Sr[(32 + r0) * S_PITCH + 2] : 0.f;                             \
          const float s3 = c >= 3 ? Sr[(48 + r0) * S_PITCH + 3] : 0.f;                             \
          y_[t2] = (Sr[r0 * S_PITCH] + s1) + (s2 + s3);                                            \
        }                                                                                          \
        ares[r2] = hadd2_bf16(pack_bf16(y_[0], y_[1]), hmul2_bf16(__byte_perm(rv[7 - (r2)], rv[7 - (r2)], 0x1032), dk2)); \
      }
      auto store_a = [&](int ch) {
        uint4* ap = (uint4*)(smem + SM_X + CV_R + ch * R_CH + c * 32);
        ap[0] = make_uint4(ares[0], ares[1], ares[2], ares[3]);
        ap[1] = make_uint4(ares[4], ares[5], ares[6], ares[7]);
        fence_async();
      };
      const uint32_t eoff = ((g & 1) ? E_COPY : 0) + (16 * w + (g & ~1) + 2 * q) * 2;
      const uint32_t dkA = dup_lo(dsk), dkB = dup_hi(dsk);
      {
        const int ch = 2 * wg;
        const uint32_t ebase = sb + SM_X + CV_E + ch * E_CH + eoff;
        const uint64_t de = mkdesc(sb + SM_X + CV_R + ch * R_CH, R_HALF, 128, 0);
        conv_load4<0>(fa, ebase, zero);
        conv_load4<4>(fb, ebase, zero);
        CONV_CHANNEL(mbar_wait(bars + 8 * (B_STF + 1), 0); mbar_wait(bars + 8 * (B_STF + 2), 0); mbar_wait(bars + 8 * (B_STF + 3), 0); mbar_wait(bars + 8 * (B_STF + 4), 0);, , )
        TM_IF(tid == 0, 14);
      }
      issue_half(accA, 6, H0{});
      issue_half(accA, 6, H1{});
      bar_sync(6 + wg, 128);
      POST(0, dkA) POST(1, dkA) POST(2, dkA) POST(3, dkA) POST(4, dkA) POST(5, dkA) POST(6, dkA) POST(7, dkA)
      store_a(2 * wg);
      __syncwarp();
      if (lane == 0) mbar_arrive(bars + 8 * B_ADONE);
      {
        const int ch = 2 * wg + 1;
        const uint32_t ebase = sb + SM_X + CV_E + ch * E_CH + eoff;
        const uint64_t de = mkdesc(sb + SM_X + CV_R + ch * R_CH, R_HALF, 128, 0);
        conv_load4<0>(fa, ebase, zero);
        conv_load4<4>(fb, ebase, zero);
        wg_wait<0>();
        send_pass(accA, 6);
        CONV_CHANNEL(bar_sync(6 + wg, 128);, , )
        bar_sync(6 + wg, 128);
        TM_IF(tid == 0, 17);
        POST(0, dkB) POST(1, dkB) POST(2, dkB) POST(3, dkB) POST(4, dkB) POST(5, dkB) POST(6, dkB) POST(7, dkB)
        store_a(ch);
        __syncwarp();
        if (lane == 0) mbar_arrive(bars + 8 * B_ADONE);
      }
#undef POST
    }
    {
      uint4 v0[4], v1[4], v2[4], v3[4];
      mbar_wait(bars + 8 * B_GOT, 0);
      part_load(v0, 1);
      part_load(v1, 2);
      part_load(v2, 3);
      part_load(v3, 4);
      issue_half(accB, 7, H0{});
      issue_half(accB, 7, H1{});
#pragma unroll
      for (int i = 0; i < 32; i++) accA[i] = 0.f;
      part_add(v0); part_load(v0, 5);
      part_add(v1); part_load(v1, 6);
      part_add(v2); part_load(v2, 7);
      part_add(v3);
      part_add(v0);
      part_add(v1);
      part_add(v2);
    }
    TM_IF(tid == 0, 28);
    mbar_wait(bars + 8 * B_ATILE, 0);
    TM_IF(tid == 0, 29);
    const int row0 = it_ * 128 + warp * 16 + g;
    const float g0 = __ldcg(g_gate + row0), g1 = __ldcg(g_gate + row0 + 8);
    uint32_t av[16];
    {
      const int dl = (lane & 7) + ((lane >> 4) << 3);
      const int chunk = 2 * (warp & 3) + ((lane >> 3) & 1);
      const uint32_t abase = sb + SM_AT + wg * 8192 + dl * 128 + ((chunk ^ (lane & 7)) << 4);
#pragma unroll
      for (int m2 = 0; m2 < 4; m2++) {
        asm volatile("ldmatrix.sync.aligned.m8n8.x4.trans.shared.b16 {%0,%1,%2,%3}, [%4];"
                     : "=r"(av[4 * m2]), "=r"(av[4 * m2 + 1]), "=r"(av[4 * m2 + 2]), "=r"(av[4 * m2 + 3]) : "r"(abase + m2 * 2048) : "memory");
      }
    }
    wg_wait<0>();
    const uint32_t gg0 = pack_bf16(g0, g0), gg1 = pack_bf16(g1, g1);
    const uint32_t og0 = pack_bf16(1.f - g0, 1.f - g0), og1 = pack_bf16(1.f - g1, 1.f - g1);
    uint32_t ov[16];
#pragma unroll
    for (int m = 0; m < 8; m++) {
      const uint32_t b0 = pack_bf16(accA[4 * m] + accB[4 * m], accA[4 * m + 1] + accB[4 * m + 1]);
      const uint32_t b1 = pack_bf16(accA[4 * m + 2] + accB[4 * m + 2], accA[4 * m + 3] + accB[4 * m + 3]);
      ov[2 * m] = hadd2_bf16(hmul2_bf16(gg0, av[2 * m]), hmul2_bf16(og0, b0));
      ov[2 * m + 1] = hadd2_bf16(hmul2_bf16(gg1, av[2 * m + 1]), hmul2_bf16(og1, b1));
    }
    {
      const uint32_t ob = sb + SM_X + CV_S + wg * S_WG + (warp & 3) * 2048;
      const int srow = (lane & 7) + ((lane >> 3) & 1) * 8;
#pragma unroll
      for (int m2 = 0; m2 < 4; m2++) {
        const int chunk = 2 * m2 + (lane >> 4);
        asm volatile("stmatrix.sync.aligned.m8n8.x4.shared.b16 [%0], {%1,%2,%3,%4};"
                     ::"r"(ob + srow * 128 + ((chunk ^ (srow & 7)) << 4)), "r"(ov[4 * m2]), "r"(ov[4 * m2 + 1]), "r"(ov[4 * m2 + 2]), "r"(ov[4 * m2 + 3]) : "memory");
      }
      __syncwarp();
#pragma unroll
      for (int i = 0; i < 4; i++) {
        const int r = 4 * i + (lane >> 3), chunk = lane & 7;
        const uint4 v = *(const uint4*)(smem + SM_X + CV_S + wg * S_WG + (warp & 3) * 2048 + r * 128 + ((chunk ^ (r & 7)) << 4));
        *(uint4*)(P.out + (it_ * 128 + warp * 16 + r) * D_ + jf * 64 + chunk * 8) = v;
      }
    }
    TM_IF(tid == 0, 30);
  }
}

typedef CUresult (*EncFn)(CUtensorMap*, CUtensorMapDataType, cuuint32_t, void*, const cuuint64_t*, const cuuint64_t*, const cuuint32_t*,
                          const cuuint32_t*, CUtensorMapInterleave, CUtensorMapSwizzle, CUtensorMapL2promotion, CUtensorMapFloatOOBfill);

struct HostState {
  bool ready;
  const void* key[4];
  Maps M;
};
HostState hs;

}

extern "C" void kernel_launch(void* const* d_in, const int* in_sizes, int n_in, void* d_out, int out_size) {
  (void)in_sizes; (void)n_in; (void)out_size;
  void* x = d_in[0];
  void* wg = d_in[8];
  void* wu = d_in[9];
  void* wd = d_in[10];
  if (!hs.ready || hs.key[0] != x || hs.key[1] != wg || hs.key[2] != wu || hs.key[3] != wd) {
    void* fn = nullptr;
    cudaDriverEntryPointQueryResult qr;
    cudaGetDriverEntryPoint("cuTensorMapEncodeTiled", &fn, cudaEnableDefault, &qr);
    EncFn enc = (EncFn)fn;
    const cuuint32_t es[3] = {1, 1, 1};
    const CUtensorMapDataType BF = CU_TENSOR_MAP_DATA_TYPE_BFLOAT16;
    const CUtensorMapInterleave IN = CU_TENSOR_MAP_INTERLEAVE_NONE;
    const CUtensorMapL2promotion PR = CU_TENSOR_MAP_L2_PROMOTION_L2_128B;
    const CUtensorMapFloatOOBfill OO = CU_TENSOR_MAP_FLOAT_OOB_FILL_NONE;
    {
      cuuint64_t gd[2] = {(cuuint64_t)D_, (cuuint64_t)L_}; cuuint64_t gs[1] = {(cuuint64_t)D_ * 2}; cuuint32_t box[2] = {64, 128};
      enc(&hs.M.X, BF, 2, x, gd, gs, box, es, IN, CU_TENSOR_MAP_SWIZZLE_128B, PR, OO);
    }
    {
      cuuint64_t gd[2] = {(cuuint64_t)F_, (cuuint64_t)D_}; cuuint64_t gs[1] = {(cuuint64_t)F_ * 2}; cuuint32_t box[2] = {64, 32};
      enc(&hs.M.Wg, BF, 2, wg, gd, gs, box, es, IN, CU_TENSOR_MAP_SWIZZLE_128B, PR, OO);
      enc(&hs.M.Wu, BF, 2, wu, gd, gs, box, es, IN, CU_TENSOR_MAP_SWIZZLE_128B, PR, OO);
      for (int o = 0; o < 2; o++) {
        cuuint64_t gd3[3] = {64, (cuuint64_t)D_, (cuuint64_t)(F_ / 64 - o)}; cuuint64_t gs3[2] = {(cuuint64_t)F_ * 2, 128};
        cuuint32_t box3[3] = {64, 32, 2};
        enc(&hs.M.Wg3[o], BF, 3, (char*)wg + 64 * o, gd3, gs3, box3, es, IN, CU_TENSOR_MAP_SWIZZLE_128B, PR, OO);
        enc(&hs.M.Wu3[o], BF, 3, (char*)wu + 64 * o, gd3, gs3, box3, es, IN, CU_TENSOR_MAP_SWIZZLE_128B, PR, OO);
      }
    }
    {
      cuuint64_t gd[2] = {(cuuint64_t)D_, (cuuint64_t)F_}; cuuint64_t gs[1] = {(cuuint64_t)D_ * 2}; cuuint32_t box[2] = {64, 112};
      enc(&hs.M.Wd, BF, 2, wd, gd, gs, box, es, IN, CU_TENSOR_MAP_SWIZZLE_128B, PR, OO);
    }
    {
      void* pa = nullptr;
      cudaGetSymbolAddress(&pa, g_aT);
      cuuint64_t gd[2] = {(cuuint64_t)L_, (cuuint64_t)D_}; cuuint64_t gs[1] = {(cuuint64_t)L_ * 2}; cuuint32_t box[2] = {64, 64};
      enc(&hs.M.AT, BF, 2, pa, gd, gs, box, es, IN, CU_TENSOR_MAP_SWIZZLE_128B, PR, OO);
    }
    cudaFuncSetAttribute(fused_kernel, cudaFuncAttributeMaxDynamicSharedMemorySize, SM_TOTAL);
    hs.key[0] = x; hs.key[1] = wg; hs.key[2] = wu; hs.key[3] = wd;
    hs.ready = true;
  }
  Params P;
  P.x = (const __nv_bfloat16*)d_in[0];
  P.log_A_real = (const __nv_bfloat16*)d_in[1];
  P.A_imag = (const __nv_bfloat16*)d_in[2];
  P.C_real = (const __nv_bfloat16*)d_in[3];
  P.C_imag = (const __nv_bfloat16*)d_in[4];
  P.log_dt = (const __nv_bfloat16*)d_in[5];
  P.D_skip = (const __nv_bfloat16*)d_in[6];
  P.gate_w = (const __nv_bfloat16*)d_in[11];
  P.w_gate = (const __nv_bfloat16*)wg;
  P.w_up = (const __nv_bfloat16*)wu;
  P.w_down = (const __nv_bfloat16*)wd;
  P.out = (__nv_bfloat16*)d_out;
  fused_kernel<<<NCTA, NTHREADS, SM_TOTAL>>>(hs.M, P);
}
```

```cpp
#include <cuda_runtime.h>
#include <cuda_bf16.h>
#include <cuda.h>
#include <stdint.h>

#define PUBMODE 2
namespace {

constexpr int L_ = 2048, D_ = 512, F_ = 1792, NS_ = 128;
constexpr int NCTA = 128;
constexpr int NTHREADS = 384;

constexpr int SM_X = 0;
constexpr int SM_RING = 131072;
constexpr int KC_STRIDE = 656;
constexpr int SM_KB = 212992;
constexpr int SM_PR = SM_KB + 4 * KC_STRIDE * 2;
constexpr int SM_BAR = SM_PR + 512 * 24;
constexpr int SM_TOTAL = SM_BAR + 512;
constexpr int CV_R = 0;
constexpr int R_HALF = 156 * 16;
constexpr int R_CH = 2 * R_HALF;
constexpr int CV_E = 4 * R_CH;
constexpr int E_COPY = 4160;
constexpr int E_CH = 2 * E_COPY;
constexpr int CV_S = CV_E + 4 * E_CH;
constexpr int S_PITCH = 136;
constexpr int S_WG = 4 * 16 * S_PITCH * 4;
constexpr int SM_AT = SM_X;
static_assert(CV_S + 2 * S_WG + 8192 <= 131072, "conv region");
static_assert(SM_PR % 128 == 0, "alignment");

constexpr int B_FULL = 0, B_EMPTY = 5, B_XFULL = 10, B_XFREE = 18, B_ATILE = 26, B_RRDY = 27, B_ADONE = 28, B_KPART = 29, B_KSUM = 30, B_SENT = 35, B_GOT = 43, B_STF = 51;

__device__ uint4 g_part[16 * 8 * 8 * 8 * 4 * 32];
__device__ uint32_t g_flag[16 * 8 * 8];
__device__ __align__(1024) __nv_bfloat16 g_aT[D_ * L_];
__device__ float g_gate[L_];
__device__ uint32_t g_done1;
__device__ uint32_t g_cnt[8 * 32];
__device__ uint32_t g_exit;
__device__ uint32_t g_zero;
__device__ uint32_t g_epoch;

#define TM_IF(cond, idx) do {} while (0)
#define FAIL(a, ph) break
#define SPIN_LIMIT (1 << 22)
#define MBAR_LIMIT (1 << 20)
__device__ __forceinline__ uint32_t smem_u32(const void* p) { return (uint32_t)__cvta_generic_to_shared(p); }
__device__ __forceinline__ void mbar_init(uint32_t a, uint32_t c) { asm volatile("mbarrier.init.shared::cta.b64 [%0], %1;" ::"r"(a), "r"(c) : "memory"); }
__device__ __forceinline__ void mbar_expect(uint32_t a, uint32_t bytes) { asm volatile("mbarrier.arrive.expect_tx.shared::cta.b64 _, [%0], %1;" ::"r"(a), "r"(bytes) : "memory"); }
__device__ __forceinline__ void mbar_arrive(uint32_t a) { asm volatile("mbarrier.arrive.shared::cta.b64 _, [%0];" ::"r"(a) : "memory"); }
__device__ __forceinline__ void mbar_wait(uint32_t a, uint32_t ph) {
  asm volatile("{\n.reg .pred p;\n.reg .u32 c;\nmov.u32 c, 0;\nLW:\nmbarrier.try_wait.parity.shared::cta.b64 p, [%0], %1, %2;\n@p bra LD;\n"
               "add.u32 c, c, 1;\nsetp.lt.u32 p, c, 1048576;\n@p bra LW;\nLD:\n}" ::"r"(a), "r"(ph), "r"(20000u) : "memory");
}
template <int NS> __device__ __forceinline__ void mbar_wait_lazy(uint32_t a, uint32_t ph) {
  asm volatile("{\n.reg .pred p;\n.reg .u32 c;\nmov.u32 c, 0;\nLW:\nmbarrier.test_wait.parity.shared::cta.b64 p, [%0], %1;\n@p bra LD;\n"
               "nanosleep.u32 %2;\nadd.u32 c, c, 1;\nsetp.lt.u32 p, c, 4194304;\n@p bra LW;\nLD:\n}" ::"r"(a), "r"(ph), "n"(NS) : "memory");
}
__device__ __forceinline__ void tma2d(uint32_t dst, const CUtensorMap* m, int c0, int c1, uint32_t bar) {
  asm volatile("cp.async.bulk.tensor.2d.shared::cluster.global.mbarrier::complete_tx::bytes [%0], [%1, {%3,%4}], [%2];" ::"r"(dst), "l"(m), "r"(bar), "r"(c0), "r"(c1) : "memory");
}
__device__ __forceinline__ void tma3d(uint32_t dst, const CUtensorMap* m, int c0, int c1, int c2, uint32_t bar) {
  asm volatile("cp.async.bulk.tensor.3d.shared::cluster.global.mbarrier::complete_tx::bytes [%0], [%1, {%3,%4,%5}], [%2];" ::"r"(dst), "l"(m), "r"(bar), "r"(c0), "r"(c1), "r"(c2) : "memory");
}
__device__ __forceinline__ uint64_t mkdesc(uint32_t addr, uint32_t lbo, uint32_t sbo, uint32_t sw) {
  return (uint64_t)((addr & 0x3FFFF) >> 4) | ((uint64_t)(lbo >> 4) << 16) | ((uint64_t)(sbo >> 4) << 32) | ((uint64_t)sw << 62);
}
__device__ __forceinline__ void wg_fence() { asm volatile("wgmma.fence.sync.aligned;" ::: "memory"); }
__device__ __forceinline__ void wg_commit() { asm volatile("wgmma.commit_group.sync.aligned;" ::: "memory"); }
template <int N> __device__ __forceinline__ void wg_wait() { asm volatile("wgmma.wait_group.sync.aligned %0;" ::"n"(N) : "memory"); }
__device__ __forceinline__ void zero_reg(float& x) { asm volatile("mov.f32 %0, 0f00000000;" : "=f"(x)); }
__device__ __forceinline__ void movf(float& d, float s) { asm volatile("mov.f32 %0, %1;" : "=f"(d) : "f"(s)); }
__device__ __forceinline__ void bar_sync(int id, int n) { asm volatile("bar.sync %0, %1;" ::"r"(id), "r"(n) : "memory"); }
__device__ __forceinline__ void fence_async() { asm volatile("fence.proxy.async.shared::cta;" ::: "memory"); }
__device__ __forceinline__ uint32_t pack_bf16(float lo, float hi) {
  uint32_t r;
  asm("cvt.rn.bf16x2.f32 %0, %1, %2;" : "=r"(r) : "f"(hi), "f"(lo));
  return r;
}
__device__ __forceinline__ uint32_t hmul2_bf16(uint32_t a, uint32_t b) {
  uint32_t r;
  asm("mul.rn.bf16x2 %0, %1, %2;" : "=r"(r) : "r"(a), "r"(b));
  return r;
}
__device__ __forceinline__ uint32_t hadd2_bf16(uint32_t a, uint32_t b) {
  uint32_t r;
  asm("add.rn.bf16x2 %0, %1, %2;" : "=r"(r) : "r"(a), "r"(b));
  return r;
}
__device__ __forceinline__ float bf_lo(uint32_t v) { return __uint_as_float(v << 16); }
__device__ __forceinline__ float bf_hi(uint32_t v) { return __uint_as_float(v & 0xFFFF0000u); }
__device__ __forceinline__ float bf16r(float x) { return __bfloat162float(__float2bfloat16_rn(x)); }
__device__ __forceinline__ float ldbf(const __nv_bfloat16* p) { return __bfloat162float(*p); }
__device__ __forceinline__ uint32_t ld_acquire(const uint32_t* p) {
  uint32_t v;
  asm volatile("ld.acquire.gpu.global.u32 %0, [%1];" : "=r"(v) : "l"(p) : "memory");
  return v;
}
__device__ __forceinline__ void st_release(uint32_t* p, uint32_t v) { asm volatile("st.release.gpu.global.u32 [%0], %1;" ::"l"(p), "r"(v) : "memory"); }
__device__ __forceinline__ uint4 ld_cg4(const uint4* p) {
  uint4 v;
  asm volatile("ld.global.cg.v4.u32 {%0,%1,%2,%3}, [%4];" : "=r"(v.x), "=r"(v.y), "=r"(v.z), "=r"(v.w) : "l"(p) : "memory");
  return v;
}
__device__ __forceinline__ uint32_t ld_cg1(const void* p) {
  uint32_t v;
  asm volatile("ld.global.cg.u32 %0, [%1];" : "=r"(v) : "l"(p) : "memory");
  return v;
}
__device__ __forceinline__ uint32_t lds32(uint32_t a) {
  uint32_t v;
  asm volatile("ld.shared.u32 %0, [%1];" : "=r"(v) : "r"(a) : "memory");
  return v;
}
__device__ __forceinline__ void ldsm4(uint32_t (&r)[4], uint32_t a) {
  asm volatile("ldmatrix.sync.aligned.m8n8.x4.shared.b16 {%0,%1,%2,%3}, [%4];" : "=r"(r[0]), "=r"(r[1]), "=r"(r[2]), "=r"(r[3]) : "r"(a) : "memory");
}
__device__ __forceinline__ uint32_t pack_f16(float lo, float hi) {
  uint32_t r;
  asm("cvt.rn.f16x2.f32 %0, %1, %2;" : "=r"(r) : "f"(hi), "f"(lo));
  return r;
}

__device__ __forceinline__ void wgmma_ss_n256(float (&d)[128], uint64_t da, uint64_t db) {
  asm volatile("wgmma.mma_async.sync.aligned.m64n256k16.f32.bf16.bf16 {%0, %1, %2, %3, %4, %5, %6, %7, %8, %9, %10, %11, %12, %13, %14, %15, %16, %17, %18, %19, %20, %21, %22, %23, %24, %25, %26, %27, %28, %29, %30, %31, %32, %33, %34, %35, %36, %37, %38, %39, %40, %41, %42, %43, %44, %45, %46, %47, %48, %49, %50, %51, %52, %53, %54, %55, %56, %57, %58, %59, %60, %61, %62, %63, %64, %65, %66, %67, %68, %69, %70, %71, %72, %73, %74, %75, %76, %77, %78, %79, %80, %81, %82, %83, %84, %85, %86, %87, %88, %89, %90, %91, %92, %93, %94, %95, %96, %97, %98, %99, %100, %101, %102, %103, %104, %105, %106, %107, %108, %109, %110, %111, %112, %113, %114, %115, %116, %117, %118, %119, %120, %121, %122, %123, %124, %125, %126, %127}, %128, %129, 1, 1, 1, 0, 1;"
    : "+f"(d[0]), "+f"(d[1]), "+f"(d[2]), "+f"(d[3]), "+f"(d[4]), "+f"(d[5]), "+f"(d[6]), "+f"(d[7]), "+f"(d[8]), "+f"(d[9]), "+f"(d[10]), "+f"(d[11]), "+f"(d[12]), "+f"(d[13]), "+f"(d[14]), "+f"(d[15]), "+f"(d[16]), "+f"(d[17]), "+f"(d[18]), "+f"(d[19]), "+f"(d[20]), "+f"(d[21]), "+f"(d[22]), "+f"(d[23]), "+f"(d[24]), "+f"(d[25]), "+f"(d[26]), "+f"(d[27]), "+f"(d[28]), "+f"(d[29]), "+f"(d[30]), "+f"(d[31]), "+f"(d[32]), "+f"(d[33]), "+f"(d[34]), "+f"(d[35]), "+f"(d[36]), "+f"(d[37]), "+f"(d[38]), "+f"(d[39]), "+f"(d[40]), "+f"(d[41]), "+f"(d[42]), "+f"(d[43]), "+f"(d[44]), "+f"(d[45]), "+f"(d[46]), "+f"(d[47]), "+f"(d[48]), "+f"(d[49]), "+f"(d[50]), "+f"(d[51]), "+f"(d[52]), "+f"(d[53]), "+f"(d[54]), "+f"(d[55]), "+f"(d[56]), "+f"(d[57]), "+f"(d[58]), "+f"(d[59]), "+f"(d[60]), "+f"(d[61]), "+f"(d[62]), "+f"(d[63]), "+f"(d[64]), "+f"(d[65]), "+f"(d[66]), "+f"(d[67]), "+f"(d[68]), "+f"(d[69]), "+f"(d[70]), "+f"(d[71]), "+f"(d[72]), "+f"(d[73]), "+f"(d[74]), "+f"(d[75]), "+f"(d[76]), "+f"(d[77]), "+f"(d[78]), "+f"(d[79]), "+f"(d[80]), "+f"(d[81]), "+f"(d[82]), "+f"(d[83]), "+f"(d[84]), "+f"(d[85]), "+f"(d[86]), "+f"(d[87]), "+f"(d[88]), "+f"(d[89]), "+f"(d[90]), "+f"(d[91]), "+f"(d[92]), "+f"(d[93]), "+f"(d[94]), "+f"(d[95]), "+f"(d[96]), "+f"(d[97]), "+f"(d[98]), "+f"(d[99]), "+f"(d[100]), "+f"(d[101]), "+f"(d[102]), "+f"(d[103]), "+f"(d[104]), "+f"(d[105]), "+f"(d[106]), "+f"(d[107]), "+f"(d[108]), "+f"(d[109]), "+f"(d[110]), "+f"(d[111]), "+f"(d[112]), "+f"(d[113]), "+f"(d[114]), "+f"(d[115]), "+f"(d[116]), "+f"(d[117]), "+f"(d[118]), "+f"(d[119]), "+f"(d[120]), "+f"(d[121]), "+f"(d[122]), "+f"(d[123]), "+f"(d[124]), "+f"(d[125]), "+f"(d[126]), "+f"(d[127]) : "l"(da), "l"(db));
}
__device__ __forceinline__ void wgmma_rs_n96(float (&d)[48], uint32_t a0, uint32_t a1, uint32_t a2, uint32_t a3, uint64_t db) {
  asm volatile("wgmma.mma_async.sync.aligned.m64n96k16.f32.bf16.bf16 {%0, %1, %2, %3, %4, %5, %6, %7, %8, %9, %10, %11, %12, %13, %14, %15, %16, %17, %18, %19, %20, %21, %22, %23, %24, %25, %26, %27, %28, %29, %30, %31, %32, %33, %34, %35, %36, %37, %38, %39, %40, %41, %42, %43, %44, %45, %46, %47}, {%48,%49,%50,%51}, %52, 1, 1, 1, 1;"
    : "+f"(d[0]), "+f"(d[1]), "+f"(d[2]), "+f"(d[3]), "+f"(d[4]), "+f"(d[5]), "+f"(d[6]), "+f"(d[7]), "+f"(d[8]), "+f"(d[9]), "+f"(d[10]), "+f"(d[11]), "+f"(d[12]), "+f"(d[13]), "+f"(d[14]), "+f"(d[15]), "+f"(d[16]), "+f"(d[17]), "+f"(d[18]), "+f"(d[19]), "+f"(d[20]), "+f"(d[21]), "+f"(d[22]), "+f"(d[23]), "+f"(d[24]), "+f"(d[25]), "+f"(d[26]), "+f"(d[27]), "+f"(d[28]), "+f"(d[29]), "+f"(d[30]), "+f"(d[31]), "+f"(d[32]), "+f"(d[33]), "+f"(d[34]), "+f"(d[35]), "+f"(d[36]), "+f"(d[37]), "+f"(d[38]), "+f"(d[39]), "+f"(d[40]), "+f"(d[41]), "+f"(d[42]), "+f"(d[43]), "+f"(d[44]), "+f"(d[45]), "+f"(d[46]), "+f"(d[47]) : "r"(a0), "r"(a1), "r"(a2), "r"(a3), "l"(db));
}
__device__ __forceinline__ void wgmma_rs_n64t(float (&d)[32], uint32_t a0, uint32_t a1, uint32_t a2, uint32_t a3, uint64_t db) {
  asm volatile("wgmma.mma_async.sync.aligned.m64n64k16.f32.bf16.bf16 {%0, %1, %2, %3, %4, %5, %6, %7, %8, %9, %10, %11, %12, %13, %14, %15, %16, %17, %18, %19, %20, %21, %22, %23, %24, %25, %26, %27, %28, %29, %30, %31}, {%32,%33,%34,%35}, %36, 1, 1, 1, 1;"
    : "+f"(d[0]), "+f"(d[1]), "+f"(d[2]), "+f"(d[3]), "+f"(d[4]), "+f"(d[5]), "+f"(d[6]), "+f"(d[7]), "+f"(d[8]), "+f"(d[9]), "+f"(d[10]), "+f"(d[11]), "+f"(d[12]), "+f"(d[13]), "+f"(d[14]), "+f"(d[15]), "+f"(d[16]), "+f"(d[17]), "+f"(d[18]), "+f"(d[19]), "+f"(d[20]), "+f"(d[21]), "+f"(d[22]), "+f"(d[23]), "+f"(d[24]), "+f"(d[25]), "+f"(d[26]), "+f"(d[27]), "+f"(d[28]), "+f"(d[29]), "+f"(d[30]), "+f"(d[31]) : "r"(a0), "r"(a1), "r"(a2), "r"(a3), "l"(db));
}
__device__ __forceinline__ void cw128z(float (&d)[64], uint32_t a0, uint32_t a1, uint32_t a2, uint32_t a3, uint64_t db) {
  asm volatile("{.reg .pred p; setp.ne.b32 p, 0, 0; wgmma.mma_async.sync.aligned.m64n128k16.f32.bf16.bf16 {%0, %1, %2, %3, %4, %5, %6, %7, %8, %9, %10, %11, %12, %13, %14, %15, %16, %17, %18, %19, %20, %21, %22, %23, %24, %25, %26, %27, %28, %29, %30, %31, %32, %33, %34, %35, %36, %37, %38, %39, %40, %41, %42, %43, %44, %45, %46, %47, %48, %49, %50, %51, %52, %53, %54, %55, %56, %57, %58, %59, %60, %61, %62, %63}, {%64,%65,%66,%67}, %68, p, 1, 1, 0;}"
    : "=f"(d[0]), "=f"(d[1]), "=f"(d[2]), "=f"(d[3]), "=f"(d[4]), "=f"(d[5]), "=f"(d[6]), "=f"(d[7]), "=f"(d[8]), "=f"(d[9]), "=f"(d[10]), "=f"(d[11]), "=f"(d[12]), "=f"(d[13]), "=f"(d[14]), "=f"(d[15]), "=f"(d[16]), "=f"(d[17]), "=f"(d[18]), "=f"(d[19]), "=f"(d[20]), "=f"(d[21]), "=f"(d[22]), "=f"(d[23]), "=f"(d[24]), "=f"(d[25]), "=f"(d[26]), "=f"(d[27]), "=f"(d[28]), "=f"(d[29]), "=f"(d[30]), "=f"(d[31]), "=f"(d[32]), "=f"(d[33]), "=f"(d[34]), "=f"(d[35]), "=f"(d[36]), "=f"(d[37]), "=f"(d[38]), "=f"(d[39]), "=f"(d[40]), "=f"(d[41]), "=f"(d[42]), "=f"(d[43]), "=f"(d[44]), "=f"(d[45]), "=f"(d[46]), "=f"(d[47]), "=f"(d[48]), "=f"(d[49]), "=f"(d[50]), "=f"(d[51]), "=f"(d[52]), "=f"(d[53]), "=f"(d[54]), "=f"(d[55]), "=f"(d[56]), "=f"(d[57]), "=f"(d[58]), "=f"(d[59]), "=f"(d[60]), "=f"(d[61]), "=f"(d[62]), "=f"(d[63]) : "r"(a0), "r"(a1), "r"(a2), "r"(a3), "l"(db));
}
__device__ __forceinline__ void cw128(float (&d)[64], uint32_t a0, uint32_t a1, uint32_t a2, uint32_t a3, uint64_t db) {
  asm volatile("wgmma.mma_async.sync.aligned.m64n128k16.f32.bf16.bf16 {%0, %1, %2, %3, %4, %5, %6, %7, %8, %9, %10, %11, %12, %13, %14, %15, %16, %17, %18, %19, %20, %21, %22, %23, %24, %25, %26, %27, %28, %29, %30, %31, %32, %33, %34, %35, %36, %37, %38, %39, %40, %41, %42, %43, %44, %45, %46, %47, %48, %49, %50, %51, %52, %53, %54, %55, %56, %57, %58, %59, %60, %61, %62, %63}, {%64,%65,%66,%67}, %68, 1, 1, 1, 0;"
    : "+f"(d[0]), "+f"(d[1]), "+f"(d[2]), "+f"(d[3]), "+f"(d[4]), "+f"(d[5]), "+f"(d[6]), "+f"(d[7]), "+f"(d[8]), "+f"(d[9]), "+f"(d[10]), "+f"(d[11]), "+f"(d[12]), "+f"(d[13]), "+f"(d[14]), "+f"(d[15]), "+f"(d[16]), "+f"(d[17]), "+f"(d[18]), "+f"(d[19]), "+f"(d[20]), "+f"(d[21]), "+f"(d[22]), "+f"(d[23]), "+f"(d[24]), "+f"(d[25]), "+f"(d[26]), "+f"(d[27]), "+f"(d[28]), "+f"(d[29]), "+f"(d[30]), "+f"(d[31]), "+f"(d[32]), "+f"(d[33]), "+f"(d[34]), "+f"(d[35]), "+f"(d[36]), "+f"(d[37]), "+f"(d[38]), "+f"(d[39]), "+f"(d[40]), "+f"(d[41]), "+f"(d[42]), "+f"(d[43]), "+f"(d[44]), "+f"(d[45]), "+f"(d[46]), "+f"(d[47]), "+f"(d[48]), "+f"(d[49]), "+f"(d[50]), "+f"(d[51]), "+f"(d[52]), "+f"(d[53]), "+f"(d[54]), "+f"(d[55]), "+f"(d[56]), "+f"(d[57]), "+f"(d[58]), "+f"(d[59]), "+f"(d[60]), "+f"(d[61]), "+f"(d[62]), "+f"(d[63]) : "r"(a0), "r"(a1), "r"(a2), "r"(a3), "l"(db));
}
__device__ __forceinline__ void cw96(float (&d)[48], uint32_t a0, uint32_t a1, uint32_t a2, uint32_t a3, uint64_t db) {
  asm volatile("wgmma.mma_async.sync.aligned.m64n96k16.f32.bf16.bf16 {%0, %1, %2, %3, %4, %5, %6, %7, %8, %9, %10, %11, %12, %13, %14, %15, %16, %17, %18, %19, %20, %21, %22, %23, %24, %25, %26, %27, %28, %29, %30, %31, %32, %33, %34, %35, %36, %37, %38, %39, %40, %41, %42, %43, %44, %45, %46, %47}, {%48,%49,%50,%51}, %52, 1, 1, 1, 0;"
    : "+f"(d[0]), "+f"(d[1]), "+f"(d[2]), "+f"(d[3]), "+f"(d[4]), "+f"(d[5]), "+f"(d[6]), "+f"(d[7]), "+f"(d[8]), "+f"(d[9]), "+f"(d[10]), "+f"(d[11]), "+f"(d[12]), "+f"(d[13]), "+f"(d[14]), "+f"(d[15]), "+f"(d[16]), "+f"(d[17]), "+f"(d[18]), "+f"(d[19]), "+f"(d[20]), "+f"(d[21]), "+f"(d[22]), "+f"(d[23]), "+f"(d[24]), "+f"(d[25]), "+f"(d[26]), "+f"(d[27]), "+f"(d[28]), "+f"(d[29]), "+f"(d[30]), "+f"(d[31]), "+f"(d[32]), "+f"(d[33]), "+f"(d[34]), "+f"(d[35]), "+f"(d[36]), "+f"(d[37]), "+f"(d[38]), "+f"(d[39]), "+f"(d[40]), "+f"(d[41]), "+f"(d[42]), "+f"(d[43]), "+f"(d[44]), "+f"(d[45]), "+f"(d[46]), "+f"(d[47]) : "r"(a0), "r"(a1), "r"(a2), "r"(a3), "l"(db));
}
__device__ __forceinline__ void cw64(float (&d)[32], uint32_t a0, uint32_t a1, uint32_t a2, uint32_t a3, uint64_t db) {
  asm volatile("wgmma.mma_async.sync.aligned.m64n64k16.f32.bf16.bf16 {%0, %1, %2, %3, %4, %5, %6, %7, %8, %9, %10, %11, %12, %13, %14, %15, %16, %17, %18, %19, %20, %21, %22, %23, %24, %25, %26, %27, %28, %29, %30, %31}, {%32,%33,%34,%35}, %36, 1, 1, 1, 0;"
    : "+f"(d[0]), "+f"(d[1]), "+f"(d[2]), "+f"(d[3]), "+f"(d[4]), "+f"(d[5]), "+f"(d[6]), "+f"(d[7]), "+f"(d[8]), "+f"(d[9]), "+f"(d[10]), "+f"(d[11]), "+f"(d[12]), "+f"(d[13]), "+f"(d[14]), "+f"(d[15]), "+f"(d[16]), "+f"(d[17]), "+f"(d[18]), "+f"(d[19]), "+f"(d[20]), "+f"(d[21]), "+f"(d[22]), "+f"(d[23]), "+f"(d[24]), "+f"(d[25]), "+f"(d[26]), "+f"(d[27]), "+f"(d[28]), "+f"(d[29]), "+f"(d[30]), "+f"(d[31]) : "r"(a0), "r"(a1), "r"(a2), "r"(a3), "l"(db));
}
__device__ __forceinline__ void cw32(float (&d)[16], uint32_t a0, uint32_t a1, uint32_t a2, uint32_t a3, uint64_t db) {
  asm volatile("wgmma.mma_async.sync.aligned.m64n32k16.f32.bf16.bf16 {%0, %1, %2, %3, %4, %5, %6, %7, %8, %9, %10, %11, %12, %13, %14, %15}, {%16,%17,%18,%19}, %20, 1, 1, 1, 0;"
    : "+f"(d[0]), "+f"(d[1]), "+f"(d[2]), "+f"(d[3]), "+f"(d[4]), "+f"(d[5]), "+f"(d[6]), "+f"(d[7]), "+f"(d[8]), "+f"(d[9]), "+f"(d[10]), "+f"(d[11]), "+f"(d[12]), "+f"(d[13]), "+f"(d[14]), "+f"(d[15]) : "r"(a0), "r"(a1), "r"(a2), "r"(a3), "l"(db));
}

struct cpx { float r, i; };
__device__ __forceinline__ cpx cmul(cpx a, cpx b) { return {fmaf(a.r, b.r, -a.i * b.i), fmaf(a.r, b.i, a.i * b.r)}; }
__device__ __forceinline__ cpx csqr(cpx a) { return {fmaf(a.r, a.r, -a.i * a.i), (a.r * a.i) * 2.f}; }
__device__ __forceinline__ cpx cmulc(cpx a, cpx b) { return {fmaf(a.r, b.r, -a.i * b.i), fmaf(-a.r, b.i, -a.i * b.r)}; }
__device__ __forceinline__ cpx cexp_fast(float re, float im) {
  float e;
  asm("ex2.approx.ftz.f32 %0, %1;" : "=f"(e) : "f"(re * 1.4426950408889634f));
  float k = rintf(im * 0.15915494309189535f);
  float r = fmaf(k, -6.2831854820251465f, im);
  r = fmaf(k, 1.7484555314695172e-07f, r);
  float s, c;
  asm("sin.approx.f32 %0, %1;" : "=f"(s) : "f"(r));
  asm("cos.approx.f32 %0, %1;" : "=f"(c) : "f"(r));
  return {e * c, e * s};
}

struct KOps { uint32_t xa[5], xb[5], y[4]; };
__device__ __forceinline__ void kgen_ops(KOps& o, const float4 pr, const float2 qq, const float gf) {
  const cpx C = {pr.z, pr.w};
  const cpx Q = {qq.x, qq.y};
  const cpx V0 = cexp_fast(pr.x * gf, pr.y * gf);
  const cpx V1 = csqr(V0), V2 = csqr(V1), V3 = csqr(V2);
  const cpx Y0 = cmulc(C, V0), Y1 = cmulc(C, V1), Y2 = cmulc(C, V2), Y3 = cmulc(C, V3);
  o.y[0] = pack_f16(Y0.r, Y0.i); o.y[1] = pack_f16(Y1.r, Y1.i); o.y[2] = pack_f16(Y2.r, Y2.i); o.y[3] = pack_f16(Y3.r, Y3.i);
  const cpx Xb = cmul(V3, Q);
  cpx Xc = cmul(Xb, Q), Xd = cmul(Xc, Q);
  o.xa[0] = pack_f16(V3.r, V3.i); o.xb[0] = pack_f16(Xb.r, Xb.i);
  o.xa[1] = pack_f16(Xc.r, Xc.i); o.xb[1] = pack_f16(Xd.r, Xd.i);
#pragma unroll
  for (int k = 2; k < 5; k++) {
    Xc = csqr(Xc); Xd = csqr(Xd);
    o.xa[k] = pack_f16(Xc.r, Xc.i); o.xb[k] = pack_f16(Xd.r, Xd.i);
  }
}
__device__ __forceinline__ void kgen_mma(float (&T)[5][4], const KOps& a, const KOps& b) {
  asm("mma.sync.aligned.m16n8k16.row.col.f32.f16.f16.f32 {%0,%1,%2,%3}, {%20,%21,%22,%23}, {%40,%41}, {%0,%1,%2,%3};\n"
      "mma.sync.aligned.m16n8k16.row.col.f32.f16.f16.f32 {%4,%5,%6,%7}, {%24,%25,%26,%27}, {%40,%41}, {%4,%5,%6,%7};\n"
      "mma.sync.aligned.m16n8k16.row.col.f32.f16.f16.f32 {%8,%9,%10,%11}, {%28,%29,%30,%31}, {%42,%43}, {%8,%9,%10,%11};\n"
      "mma.sync.aligned.m16n8k16.row.col.f32.f16.f16.f32 {%12,%13,%14,%15}, {%32,%33,%34,%35}, {%44,%45}, {%12,%13,%14,%15};\n"
      "mma.sync.aligned.m16n8k16.row.col.f32.f16.f16.f32 {%16,%17,%18,%19}, {%36,%37,%38,%39}, {%46,%47}, {%16,%17,%18,%19};\n"
      : "+f"(T[0][0]), "+f"(T[0][1]), "+f"(T[0][2]), "+f"(T[0][3]), "+f"(T[1][0]), "+f"(T[1][1]), "+f"(T[1][2]), "+f"(T[1][3]),
        "+f"(T[2][0]), "+f"(T[2][1]), "+f"(T[2][2]), "+f"(T[2][3]), "+f"(T[3][0]), "+f"(T[3][1]), "+f"(T[3][2]), "+f"(T[3][3]),
        "+f"(T[4][0]), "+f"(T[4][1]), "+f"(T[4][2]), "+f"(T[4][3])
      : "r"(a.xa[0]), "r"(a.xb[0]), "r"(b.xa[0]), "r"(b.xb[0]), "r"(a.xa[1]), "r"(a.xb[1]), "r"(b.xa[1]), "r"(b.xb[1]),
        "r"(a.xa[2]), "r"(a.xb[2]), "r"(b.xa[2]), "r"(b.xb[2]), "r"(a.xa[3]), "r"(a.xb[3]), "r"(b.xa[3]), "r"(b.xb[3]),
        "r"(a.xa[4]), "r"(a.xb[4]), "r"(b.xa[4]), "r"(b.xb[4]),
        "r"(a.y[0]), "r"(b.y[0]), "r"(a.y[1]), "r"(b.y[1]), "r"(a.y[2]), "r"(b.y[2]), "r"(a.y[3]), "r"(b.y[3]));
}

template <int J0> __device__ __forceinline__ void conv_load4(uint32_t (&f)[4][4], uint32_t ebase, uint32_t zero) {
#pragma unroll
  for (int t = 0; t < 4; t++) {
    f[t][0] = lds32(ebase + (J0 + t) * 128);
    f[t][1] = lds32(ebase + (J0 + t) * 128 + 16);
    f[t][3] = lds32(ebase + (J0 + t) * 128 + 32);
  }
#pragma unroll
  for (int t = 0; t < 4; t++)
    asm volatile("xor.b32 %0, %1, %2;" : "=r"(f[t][2]) : "r"(f[t][1]), "r"(zero));
}
#define CONV_GRP(FN, ACC, J0, F)                                                             \
  wg_fence();                                                                                \
  FN(ACC, F[0][0], F[0][1], F[0][2], F[0][3], de + 4 * (J0));                                \
  FN(ACC, F[1][0], F[1][1], F[1][2], F[1][3], de + 4 * (J0 + 1));                            \
  FN(ACC, F[2][0], F[2][1], F[2][2], F[2][3], de + 4 * (J0 + 2));                            \
  FN(ACC, F[3][0], F[3][1], F[3][2], F[3][3], de + 4 * (J0 + 3));                            \
  wg_commit();
#define CONV_STAGE(ACC, M0)                                                                  \
  _Pragma("unroll") for (int m = (M0); m < (M0) + 4; m++) {                                  \
    *(float2*)(Sw + 8 * m) = make_float2(ACC[4 * m], ACC[4 * m + 1]);                        \
    *(float2*)(Sw + 8 * S_PITCH + 8 * m) = make_float2(ACC[4 * m + 2], ACC[4 * m + 3]);      \
  }
#define CONV_CHANNEL(PRE, MID1, MID2)                                                                    \
  {                                                                                          \
    float a128[64], a96[48], a64[32], a32[16];                                               \
    wg_fence();                                                                              \
    cw128z(a128, fa[0][0], fa[0][1], fa[0][2], fa[0][3], de);                                \
    cw128(a128, fa[1][0], fa[1][1], fa[1][2], fa[1][3], de + 4);                             \
    cw128(a128, fa[2][0], fa[2][1], fa[2][2], fa[2][3], de + 8);                             \
    cw128(a128, fa[3][0], fa[3][1], fa[3][2], fa[3][3], de + 12);                            \
    wg_commit();                                                                             \
    CONV_GRP(cw128, a128, 4, fb)                                                             \
    MID1                                                                                     \
    wg_wait<1>(); conv_load4<8>(fa, ebase, zero);                                            \
    wg_wait<0>(); conv_load4<12>(fb, ebase, zero);                                           \
    _Pragma("unroll") for (int i = 0; i < 48; i++) movf(a96[i], a128[i]);                       \
    CONV_GRP(cw96, a96, 8, fa)                                                               \
    CONV_GRP(cw96, a96, 12, fb)                                                              \
    MID2                                                                                     \
    PRE                                                                                      \
    CONV_STAGE(a128, 12)                                                                     \
    wg_wait<1>(); conv_load4<16>(fa, ebase, zero);                                           \
    wg_wait<0>(); conv_load4<20>(fb, ebase, zero);                                           \
    _Pragma("unroll") for (int i = 0; i < 32; i++) movf(a64[i], a96[i]);                        \
    CONV_GRP(cw64, a64, 16, fa)                                                              \
    CONV_GRP(cw64, a64, 20, fb)                                                              \
    CONV_STAGE(a96, 8)                                                                       \
    wg_wait<1>(); conv_load4<24>(fa, ebase, zero);                                           \
    wg_wait<0>(); conv_load4<28>(fb, ebase, zero);                                           \
    _Pragma("unroll") for (int i = 0; i < 16; i++) movf(a32[i], a64[i]);                        \
    CONV_GRP(cw32, a32, 24, fa)                                                              \
    CONV_GRP(cw32, a32, 28, fb)                                                              \
    CONV_STAGE(a64, 4)                                                                       \
    load_u(ch);                                                                              \
    wg_wait<0>();                                                                            \
    CONV_STAGE(a32, 0)                                                                       \
  }

__device__ __forceinline__ int part_slot(int s, int v) {
  if (s == 6) return CV_E + 2 * v * E_CH;
  if (s == 5) return v ? (SM_PR - SM_X) : (CV_S + 2 * S_WG);
  return CV_S + v * S_WG + (s & 3) * 8192;
}
template <int V> struct IC { static constexpr int value = V; };

struct Params {
  const __nv_bfloat16* x;
  const __nv_bfloat16* log_A_real;
  const __nv_bfloat16* A_imag;
  const __nv_bfloat16* C_real;
  const __nv_bfloat16* C_imag;
  const __nv_bfloat16* log_dt;
  const __nv_bfloat16* D_skip;
  const __nv_bfloat16* gate_w;
  const __nv_bfloat16* w_gate;
  const __nv_bfloat16* w_up;
  const __nv_bfloat16* w_down;
  __nv_bfloat16* out;
};

struct Maps {
  CUtensorMap X, Wg, Wu, Wg3[2], Wu3[2], Wd, AT;
};

__device__ __forceinline__ uint32_t ld_epoch() { return *(volatile uint32_t*)&g_epoch; }
__device__ __forceinline__ uint32_t dup_lo(uint32_t w) { return __byte_perm(w, w, 0x1010); }
__device__ __forceinline__ uint32_t dup_hi(uint32_t w) { return __byte_perm(w, w, 0x3232); }

__global__ void __launch_bounds__(NTHREADS, 1)
fused_kernel(const __grid_constant__ Maps M, const Params P) {
  extern __shared__ __align__(1024) uint8_t smem[];
  const uint32_t sb = smem_u32(smem);
  const uint32_t bars = sb + SM_BAR;
  const int tid = threadIdx.x;
  const int warp = __shfl_sync(0xffffffffu, tid >> 5, 0), lane = tid & 31;
  const int b = blockIdx.x;
  const int cl = b >> 1;
  const int jf = cl & 7;
  const int it_ = ((cl >> 3) << 1) | (b & 1);
  const int d0 = b * 4;

  const int kch = warp / 3, kpart = warp - 3 * kch;
  const int kk0 = kpart == 0 ? 0 : (kpart == 1 ? 6 : 11), nks = kpart == 0 ? 6 : 5;
  uint32_t pw0[2], pw1[2], pldt;
  {
    unsigned short raw[9];
    int n0 = 8 * kk0 + lane, n1 = n0 + 32;
    n0 = (d0 + kch) * NS_ + n0;
    n1 = (d0 + kch) * NS_ + (n1 < NS_ ? n1 : NS_ - 1);
    asm volatile("ld.global.nc.u16 %0, [%9];\n\tld.global.nc.u16 %1, [%10];\n\tld.global.nc.u16 %2, [%11];\n\t"
                 "ld.global.nc.u16 %3, [%12];\n\tld.global.nc.u16 %4, [%13];\n\tld.global.nc.u16 %5, [%14];\n\t"
                 "ld.global.nc.u16 %6, [%15];\n\tld.global.nc.u16 %7, [%16];\n\tld.global.nc.u16 %8, [%17];"
                 : "=h"(raw[0]), "=h"(raw[1]), "=h"(raw[2]), "=h"(raw[3]), "=h"(raw[4]), "=h"(raw[5]), "=h"(raw[6]), "=h"(raw[7]), "=h"(raw[8])
                 : "l"(P.log_A_real + n0), "l"(P.A_imag + n0), "l"(P.C_real + n0), "l"(P.C_imag + n0),
                   "l"(P.log_A_real + n1), "l"(P.A_imag + n1), "l"(P.C_real + n1), "l"(P.C_imag + n1), "l"(P.log_dt + d0 + kch));
  if (lane == 0) {
    if (warp == 8) {
      mbar_init(bars + 8 * (B_FULL + 0), 1); mbar_init(bars + 8 * (B_FULL + 2), 1); mbar_init(bars + 8 * (B_FULL + 4), 1);
      mbar_init(bars + 8 * (B_XFULL + 0), 1); mbar_init(bars + 8 * (B_XFULL + 2), 1); mbar_init(bars + 8 * (B_XFULL + 4), 1);
    } else if (warp == 9) {
      mbar_init(bars + 8 * (B_FULL + 1), 1); mbar_init(bars + 8 * (B_FULL + 3), 1);
      mbar_init(bars + 8 * (B_XFULL + 1), 1); mbar_init(bars + 8 * (B_XFULL + 3), 1); mbar_init(bars + 8 * (B_XFULL + 5), 1);
    } else {
      const int wi = warp < 8 ? warp : warp - 2;
#pragma unroll
      for (int r = 0; r < 5; r++) {
        int i = wi + 10 * r + 5;
        if (i >= B_XFULL) i += 6;
        uint32_t cnt = 1;
        if ((i >= B_EMPTY && i < B_EMPTY + 5) || (i >= B_XFREE && i < B_XFREE + 8) || (i >= B_SENT && i < B_SENT + 8) || i == B_ADONE) cnt = 8;
        if (i == B_RRDY || i == B_KSUM) cnt = 2;
        if (i == B_GOT) cnt = 7;
        mbar_init(bars + 8 * i, cnt);
      }
    }
    asm volatile("fence.mbarrier_init.release.cluster;" ::: "memory");
  }
  __syncwarp();
    pw0[0] = (uint32_t)raw[0] | ((uint32_t)raw[1] << 16); pw1[0] = (uint32_t)raw[2] | ((uint32_t)raw[3] << 16);
    pw0[1] = (uint32_t)raw[4] | ((uint32_t)raw[5] << 16); pw1[1] = (uint32_t)raw[6] | ((uint32_t)raw[7] << 16);
    pldt = raw[8];
  }
  TM_IF(tid == 0, 21);

  auto issue_stage = [&](int s, int slot) {
    const uint32_t dst = sb + SM_RING + slot * 16384;
    const uint32_t fb = bars + 8 * (B_FULL + slot);
    if (s < 32) {
      const int f0 = jf * 224 + ((s >> 4) << 7);
      const int k0 = (s & 15) * 32;
      mbar_expect(fb, 16384);
      if (jf == 7 && s >= 16) {
        tma2d(dst, &M.Wg, f0, k0, fb);
        tma2d(dst + 4096, &M.Wg, f0 + 64, k0, fb);
        tma2d(dst + 8192, &M.Wu, f0, k0, fb);
        tma2d(dst + 12288, &M.Wu, f0 + 64, k0, fb);
      } else {
        tma3d(dst, &M.Wg3[jf & 1], 0, k0, f0 >> 6, fb);
        tma3d(dst + 8192, &M.Wu3[jf & 1], 0, k0, f0 >> 6, fb);
      }
    } else {
      const int s2 = s - 32;
      const int p = (jf + 1 + (s2 >> 1)) & 7;
      mbar_expect(fb, 14336);
      tma2d(dst, &M.Wd, p * 64, jf * 224 + (s2 & 1) * 112, fb);
    }
  };
  auto issue_x = [&](int kb) {
    mbar_expect(bars + 8 * (B_XFULL + kb), 16384);
    tma2d(sb + SM_X + kb * 16384, &M.X, kb * 64, it_ * 128, bars + 8 * (B_XFULL + kb));
  };
  {
    const int g = lane >> 2, q = lane & 3;
    const float dtf = bf16r(expf(bf_lo(pldt)));
    const int pro = kch * 128 + 8 * kk0;
    float4* prm = (float4*)(smem + SM_PR) + pro;
    float2* prq = (float2*)(smem + SM_PR + 512 * 16) + pro;
    const bool valid1 = lane + 32 < 8 * nks;
    float m0 = fmaxf(fmaxf(fabsf(bf_lo(pw1[0])), fabsf(bf_hi(pw1[0]))), fmaxf(fabsf(bf_lo(pw1[1])), fabsf(bf_hi(pw1[1])))) * dtf;
#pragma unroll
    for (int o = 16; o > 0; o >>= 1) m0 = fmaxf(m0, __shfl_xor_sync(0xffffffffu, m0, o));
    TM_IF(tid == 0 && m0 >= 0.f, 0);
    if (m0 >= 0.f || m0 != m0) {
      if (tid == 256) {
        issue_x(0); issue_stage(0, 0); issue_stage(2, 2); issue_x(2); issue_stage(4, 4); issue_x(4);
      } else if (tid == 288) {
        issue_stage(1, 1); issue_x(1); issue_stage(3, 3); issue_x(3); issue_x(5);
      }
    }
    __syncwarp();
    const uint32_t e0 = min(max(__float_as_uint(m0) >> 23, 1u), 253u);
    const float sc = __uint_as_float((254u - e0) << 23);
    const float us = 2.f * __uint_as_float(e0 << 23);
    float pe = 0.f;
#pragma unroll
    for (int r = 0; r < 2; r++) {
      float4 v;
      v.x = -bf16r(expf(bf_lo(pw0[r]))) * dtf;
      v.y = bf_hi(pw0[r]) * dtf;
      v.z = bf_lo(pw1[r]) * dtf * sc;
      v.w = bf_hi(pw1[r]) * dtf * sc;
      const cpx Q = cexp_fast(v.x * 64.f, v.y * 64.f);
      const cpx We = cexp_fast(v.x * 2048.f, v.y * 2048.f);
      if (r == 0 || valid1) {
        pe += v.z * We.r - v.w * We.i;
        prm[lane + 32 * r] = v;
        prq[lane + 32 * r] = make_float2(Q.r, Q.i);
      }
    }
#pragma unroll
    for (int o = 16; o > 0; o >>= 1) pe += __shfl_xor_sync(0xffffffffu, pe, o);
    __syncwarp();
    TM_IF(tid == 0, 1);
    float T[5][4];
#pragma unroll
    for (int i = 0; i < 20; i++) T[i >> 2][i & 3] = 0.f;
    const float gf = (float)g;
#pragma unroll 1
    for (int ks = 0; ks < nks; ks++) {
      KOps o1, o2;
      kgen_ops(o1, prm[8 * ks + q], prq[8 * ks + q], gf);
      kgen_ops(o2, prm[8 * ks + 4 + q], prq[8 * ks + 4 + q], gf);
      kgen_mma(T, o1, o2);
    }
    float* kp = (float*)(smem + SM_X + 6 * 16384) + warp * KC_STRIDE + 8 * g + 2 * q;
#pragma unroll
    for (int k = 0; k < 5; k++) {
      *(float2*)(kp + 128 * k) = make_float2(T[k][0] * us, T[k][1] * us);
      *(float2*)(kp + 128 * k + 64) = make_float2(T[k][2] * us, T[k][3] * us);
    }
    if (lane == 0) { kp[640] = pe * us; kp[641] = 0.f; }
    TM_IF(tid == 0, 2);
  }
  __syncthreads();

  if (warp >= 8) {
    asm volatile("setmaxnreg.dec.sync.aligned.u32 104;");
    if (warp < 10) {
      if (lane == 0) {
        int slot = (warp == 8) ? 1 : 0;
        uint32_t ph = 0;
#pragma unroll 1
        for (int s = (warp == 8) ? 6 : 5; s < 48; s += 2) {
          if (s == 10) { mbar_wait(bars + 8 * B_KSUM, 0); issue_x(6); issue_x(7); }
          mbar_wait(bars + 8 * (B_EMPTY + slot), ph);
          issue_stage(s, slot);
          slot += 2;
          if (slot >= 5) { slot -= 5; ph ^= 1; }
        }
      }
      __syncwarp();
      {
        const uint4 gw0 = *(const uint4*)(P.gate_w + lane * 16);
        const uint4 gw1 = *(const uint4*)(P.gate_w + lane * 16 + 8);
        uint4 xa[8], xb[8];
#pragma unroll
        for (int i = 0; i < 8; i++) {
          xa[i] = *(const uint4*)(P.x + (b * 16 + (warp - 8) * 8 + i) * D_ + lane * 16);
          xb[i] = *(const uint4*)(P.x + (b * 16 + (warp - 8) * 8 + i) * D_ + lane * 16 + 8);
        }
        float sg[8];
#pragma unroll
        for (int i = 0; i < 8; i++) {
          const uint32_t pr[8] = {hmul2_bf16(xa[i].x, gw0.x), hmul2_bf16(xa[i].y, gw0.y), hmul2_bf16(xa[i].z, gw0.z), hmul2_bf16(xa[i].w, gw0.w),
                                  hmul2_bf16(xb[i].x, gw1.x), hmul2_bf16(xb[i].y, gw1.y), hmul2_bf16(xb[i].z, gw1.z), hmul2_bf16(xb[i].w, gw1.w)};
          float s = 0.f;
#pragma unroll
          for (int k = 0; k < 8; k++) s += bf_lo(pr[k]) + bf_hi(pr[k]);
          sg[i] = s;
        }
#pragma unroll
        for (int o = 16; o > 0; o >>= 1) {
#pragma unroll
          for (int i = 0; i < 8; i++) sg[i] += __shfl_xor_sync(0xffffffffu, sg[i], o);
        }
        float z = sg[0];
#pragma unroll
        for (int i = 1; i < 8; i++) z = (lane == i) ? sg[i] : z;
        if (lane < 8) g_gate[b * 16 + (warp - 8) * 8 + lane] = bf16r(1.f / (1.f + expf(-bf16r(z))));
      }
      bar_sync(3, 64);
      if (tid == 288) asm volatile("red.release.gpu.global.add.u32 [%0], 1;" ::"l"(&g_done1) : "memory");
      TM_IF(tid == 256, 16);
      if (warp == 8) {
        if (lane >= 1 && lane < 8) {
          const uint32_t tag = ld_epoch() + 1;
          const uint32_t* fp = g_flag + ((it_ * 8 + jf) * 8 + ((jf - lane) & 7));
          int itc = 0;
          while (ld_acquire(fp) != tag) { __nanosleep(100); if (++itc > SPIN_LIMIT) FAIL(-2, lane); }
          mbar_arrive(bars + 8 * B_GOT);
          TM_IF(lane == 7, 25);
        }
      } else if (lane == 0) {
        const uint32_t tag = ld_epoch() + 1;
#pragma unroll 1
        for (int rnd = 0; rnd < 2; rnd++) {
          if (rnd == 1) {
            int itc = 0;
            while ((int)(ld_acquire(&g_done1) - (uint32_t)NCTA * tag) < 0) { if (++itc > SPIN_LIMIT) FAIL(-1, 0); }
            mbar_wait(bars + 8 * B_ADONE, 1);
          } else {
            mbar_wait_lazy<100>(bars + 8 * B_ADONE, 0);
          }
          TM_IF(true, 24);
#pragma unroll
          for (int v = 0; v < 2; v++)
            asm volatile("cp.async.bulk.global.shared::cta.bulk_group [%0], [%1], %2;"
                         ::"l"(g_aT + (d0 + 2 * v + rnd) * L_), "r"(sb + SM_X + CV_R + (2 * v + rnd) * R_CH), "r"(4096) : "memory");
          asm volatile("cp.async.bulk.commit_group;" ::: "memory");
          asm volatile("cp.async.bulk.wait_group 0;" ::: "memory");
          asm volatile("red.relaxed.gpu.global.add.u32 [%0], 1;" ::"l"(g_cnt + 32 * (b >> 4)) : "memory");
        }
        TM_IF(true, 26);
        {
          int itc = 0;
          while ((int)(ld_acquire(g_cnt + 32 * jf) - 32u * tag) < 0) { if (++itc > SPIN_LIMIT) FAIL(-3, 0); }
        }
        TM_IF(true, 23);
        asm volatile("fence.proxy.async.global;" ::: "memory");
        mbar_expect(bars + 8 * B_ATILE, 16384);
        tma2d(sb + SM_AT, &M.AT, it_ * 128, jf * 64, bars + 8 * B_ATILE);
        tma2d(sb + SM_AT + 8192, &M.AT, it_ * 128 + 64, jf * 64, bars + 8 * B_ATILE);
      }
      __syncwarp();
    } else {
      const int w = warp - 10;
      const int wt = tid - 320;
      {
        const float2* kp = (const float2*)(smem + SM_X + 6 * 16384);
        uint32_t* kb = (uint32_t*)(smem + SM_KB);
#pragma unroll
        for (int ch = 0; ch < 4; ch++) {
#pragma unroll
          for (int i = 0; i < 6; i++) {
            const int o = wt + 64 * i;
            if (i < 5 || o < 321) {
              const float2 a0 = kp[(3 * ch) * (KC_STRIDE / 2) + o], a1 = kp[(3 * ch + 1) * (KC_STRIDE / 2) + o], a2 = kp[(3 * ch + 2) * (KC_STRIDE / 2) + o];
              kb[ch * (KC_STRIDE / 2) + o] = pack_bf16(a0.x + a1.x + a2.x, a0.y + a1.y + a2.y);
            }
          }
        }
      }
      fence_async();
      bar_sync(1, 64);
      if (lane == 0) mbar_arrive(bars + 8 * B_KSUM);
      {
        const uint32_t zz = *(volatile uint32_t*)&g_zero;
        uint2 ur[4][8];
#pragma unroll
        for (int i = 0; i < 4; i++) {
#pragma unroll
          for (int r = 0; r < 8; r++) {
            uint32_t ck;
            asm volatile("nanosleep.u32 90;\n\tmov.u32 %0, %%clock;" : "=r"(ck) :: "memory");
            asm volatile("ld.global.nc.v2.u32 {%0,%1}, [%2];" : "=r"(ur[i][r].x), "=r"(ur[i][r].y)
                         : "l"(P.x + ((wt + 64 * i) * 8 + r) * D_ + d0 + (ck & zz)));
          }
        }
        mbar_wait_lazy<200>(bars + 8 * (B_XFREE + 3), 0);
        TM_IF(wt == 0, 18);
#pragma unroll
        for (int i = 0; i < 4; i++) {
          const int item = wt + 64 * i;
          const int c = item >> 1, hh = item & 1;
#pragma unroll
          for (int ch = 0; ch < 4; ch++) {
            uint32_t v[4];
#pragma unroll
            for (int k = 0; k < 4; k++) {
              const uint32_t lo = (ch < 2) ? ur[i][7 - 2 * k].x : ur[i][7 - 2 * k].y;
              const uint32_t hi = (ch < 2) ? ur[i][6 - 2 * k].x : ur[i][6 - 2 * k].y;
              v[k] = (ch & 1) ? __byte_perm(lo, hi, 0x7632) : __byte_perm(lo, hi, 0x5410);
            }
            *(uint4*)(smem + SM_X + CV_R + ch * R_CH + (1 - hh) * R_HALF + (127 - c) * 16) = make_uint4(v[0], v[1], v[2], v[3]);
          }
        }
        if (lane < 28) {
#pragma unroll
          for (int z = 0; z < 4; z++)
            *(uint4*)(smem + SM_X + CV_R + (4 * w + z) * R_HALF + (128 + lane) * 16) = make_uint4(0, 0, 0, 0);
        }
      }
      auto part_store = [&](int s) {
        mbar_wait_lazy<100>(bars + 8 * (B_SENT + s), 0);
        const int fi = (it_ * 8 + ((jf + 1 + s) & 7)) * 8 + jf;
#pragma unroll
        for (int v = 0; v < 2; v++)
          asm volatile("cp.async.bulk.global.shared::cta.bulk_group [%0], [%1], %2;"
                       ::"l"(g_part + (size_t)fi * 1024 + v * 512), "r"(sb + SM_X + part_slot(s, v)), "r"(8192) : "memory");
        asm volatile("cp.async.bulk.commit_group;" ::: "memory");
      };
      {
#pragma unroll 1
      for (int G = w; G < 8; G += 2) {
        const int n = 32 * G + lane;
        uint4 c0[4], c1[4];
        if (G >= 4) {
#pragma unroll
          for (int ch = 0; ch < 4; ch++) {
            const uint8_t* kc = smem + SM_KB + ch * KC_STRIDE * 2;
            const uint32_t a = *(const unsigned short*)(kc + (384 + n) * 2), bb = *(const unsigned short*)(kc + (385 + n) * 2);
            const uint32_t aa = a | (a << 16), b2 = bb | (bb << 16);
            const uint32_t tie = (n & 1) ? bb : a;
            c0[ch] = make_uint4(aa, a | (tie << 16), b2, b2);
            c1[ch] = make_uint4(aa, tie | (bb << 16), b2, b2);
          }
        } else if (G >= 2) {
#pragma unroll
          for (int ch = 0; ch < 4; ch++) {
            const uint8_t* kc = smem + SM_KB + ch * KC_STRIDE * 2;
            const uint32_t w0 = *(const uint32_t*)(kc + (256 + 2 * n) * 2), w1 = *(const uint32_t*)(kc + (258 + 2 * n) * 2);
            c0[ch] = make_uint4(dup_lo(w0), dup_hi(w0), __byte_perm(w0, w1, 0x5432), dup_lo(w1));
            c1[ch] = make_uint4(w0, dup_hi(w0), dup_lo(w1), dup_lo(w1));
          }
        } else if (G == 1) {
#pragma unroll
          for (int ch = 0; ch < 4; ch++) {
            const uint8_t* kc = smem + SM_KB + ch * KC_STRIDE * 2;
            const uint2 w01 = *(const uint2*)(kc + (128 + 4 * n) * 2);
            const uint32_t w2 = *(const uint32_t*)(kc + (132 + 4 * n) * 2);
            c0[ch] = make_uint4(w01.x, dup_lo(w01.y), w01.y, dup_lo(w2));
            c1[ch] = make_uint4(__byte_perm(w01.x, w01.y, 0x5432), dup_lo(w01.y), __byte_perm(w01.y, w2, 0x5432), dup_lo(w2));
          }
        } else {
#pragma unroll
          for (int ch = 0; ch < 4; ch++) {
            const uint8_t* kc = smem + SM_KB + ch * KC_STRIDE * 2;
            const uint4 wv = *(const uint4*)(kc + (8 * n) * 2);
            const uint32_t w4 = *(const uint32_t*)(kc + (8 * n + 8) * 2);
            c0[ch] = make_uint4(__byte_perm(wv.x, wv.y, 0x5432), __byte_perm(wv.y, wv.z, 0x5432), __byte_perm(wv.z, wv.w, 0x5432), __byte_perm(wv.w, w4, 0x5432));
            c1[ch] = make_uint4(wv.y, wv.z, wv.w, (n == 31) ? dup_lo(w4) : w4);
          }
          if (lane < 8) {
            const int ch = lane >> 1, hi = lane & 1;
            const uint32_t k01 = *(const uint32_t*)(smem + SM_KB + ch * KC_STRIDE * 2);
            uint8_t* e = smem + SM_X + CV_E + ch * E_CH + hi * 16;
            *(uint4*)e = make_uint4(0, 0, 0, hi ? (k01 << 16) : 0u);
            *(uint4*)(e + E_COPY) = make_uint4(0, 0, 0, hi ? k01 : 0u);
          }
        }
#pragma unroll
        for (int ch = 0; ch < 4; ch++) {
          uint8_t* e = smem + SM_X + CV_E + ch * E_CH + (n + 2) * 16;
          *(uint4*)e = c0[ch];
          *(uint4*)(e + E_COPY) = c1[ch];
        }
      }
        fence_async();
        __syncwarp();
        if (lane == 0) mbar_arrive(bars + 8 * B_RRDY);
        TM_IF(wt == 0, 19);
      }
      if (lane == 0) {
        const uint32_t tag = ld_epoch() + 1;
        auto publish = [&](int s) {
          asm volatile("st.relaxed.gpu.global.u32 [%0], %1;" ::"l"(g_flag + ((it_ * 8 + ((jf + 1 + s) & 7)) * 8 + jf)), "r"(tag) : "memory");
          TM_IF(true, 3 + s);
        };
#pragma unroll 1
        for (int s = w; s < 7; s += 2) {
          {
            part_store(s);
            asm volatile("cp.async.bulk.wait_group.read 0;" ::: "memory");
            mbar_arrive(bars + 8 * (B_STF + s));
          }
          if (s >= 2 && s < 6) {
            asm volatile("cp.async.bulk.wait_group 1;" ::: "memory");
            publish(s - 2);
          }
          if (s >= 4) {
            asm volatile("cp.async.bulk.wait_group 0;" ::: "memory");
            publish(s);
          }
        }
      }
      __syncwarp();
    }
    bar_sync(2, 128);
    if (tid == 256) {
      const uint32_t tk = atomicAdd(&g_exit, 1u);
      if (tk == NCTA - 1) {
        g_exit = 0;
        *(volatile uint32_t*)&g_epoch = ld_epoch() + 1;
      }
    }
    TM_IF(tid == 256, 13);
  } else {
    asm volatile("setmaxnreg.inc.sync.aligned.u32 200;");
    const int wg = warp >> 2;
    const int g = lane >> 2, q = lane & 3;
    const uint32_t dsk = *(const uint32_t*)(P.D_skip + d0 + 2 * wg);
    uint32_t hf[56];
    {
      float acc[128];
#pragma unroll
      for (int i = 0; i < 128; i++) zero_reg(acc[i]);
#pragma unroll 1
      for (int st = 0; st < 16; st++) {
        const int slot = st % 5;
        if ((st & 1) == 0) mbar_wait(bars + 8 * (B_XFULL + (st >> 1)), 0);
        mbar_wait(bars + 8 * (B_FULL + slot), (st / 5) & 1);
        const uint64_t da = mkdesc(sb + SM_X + (st >> 1) * 16384 + wg * 8192 + (st & 1) * 64, 16, 1024, 1);
        const uint64_t db = mkdesc(sb + SM_RING + slot * 16384, 4096, 1024, 1);
        wg_fence();
        wgmma_ss_n256(acc, da, db);
        wgmma_ss_n256(acc, da + 2, db + 128);
        wg_commit();
        if (st > 0) {
          wg_wait<1>();
          if (lane == 0) mbar_arrive(bars + 8 * (B_EMPTY + (st - 1) % 5));
        }
      }
      wg_wait<0>();
      if (lane == 0) mbar_arrive(bars + 8 * (B_EMPTY + 15 % 5));
#pragma unroll
      for (int m = 0; m < 16; m++) {
        hf[2 * m] = hmul2_bf16(pack_bf16(acc[4 * m], acc[4 * m + 1]), pack_bf16(acc[64 + 4 * m], acc[64 + 4 * m + 1]));
        hf[2 * m + 1] = hmul2_bf16(pack_bf16(acc[4 * m + 2], acc[4 * m + 3]), pack_bf16(acc[64 + 4 * m + 2], acc[64 + 4 * m + 3]));
      }
    }
    float accA[32], accB[32];
    auto issue_half = [&](float (&acc)[32], int s, auto half_tag) {
      constexpr int half = decltype(half_tag)::value;
      if (half == 0) {
#pragma unroll
        for (int i = 0; i < 32; i++) zero_reg(acc[i]);
      }
      const int st = 32 + 2 * s + half;
      const int slot = st % 5;
      mbar_wait(bars + 8 * (B_FULL + slot), (st / 5) & 1);
      uint32_t sbase;
      asm volatile("mov.b32 %0, %1;" : "=r"(sbase) : "r"(sb + SM_RING + slot * 16384));
      const uint64_t db = mkdesc(sbase, 1024, 1024, 1);
      wg_fence();
#pragma unroll
      for (int k = 0; k < 7; k++) {
        const int ks = 7 * half + k;
        wgmma_rs_n64t(acc, hf[4 * ks], hf[4 * ks + 1], hf[4 * ks + 2], hf[4 * ks + 3], db + k * 128);
      }
      wg_commit();
    };
    auto release = [&](int st) { if (lane == 0) mbar_arrive(bars + 8 * (B_EMPTY + st % 5)); };
    using H0 = IC<0>;
    using H1 = IC<1>;
    {
      float accg[48], accu[48];
#pragma unroll
      for (int i = 0; i < 48; i++) { zero_reg(accg[i]); zero_reg(accu[i]); }
      const uint32_t xrow = sb + SM_X + (wg * 64 + (warp & 3) * 16 + (lane & 15)) * 128;
      const uint32_t xsw = lane & 7, xhi = lane >> 4;
      uint32_t a0[4], a1[4], a2[4], a3[4];
#pragma unroll 1
      for (int kb = 0; kb < 8; kb++) {
        const uint32_t xb = xrow + kb * 16384;
        {
          const int st = 16 + 2 * kb, slot = st % 5;
          ldsm4(a0, xb + (((0 + xhi) ^ xsw) << 4));
          ldsm4(a1, xb + (((2 + xhi) ^ xsw) << 4));
          mbar_wait(bars + 8 * (B_FULL + slot), (st / 5) & 1);
          const uint64_t db = mkdesc(sb + SM_RING + slot * 16384, 4096, 1024, 1);
          wg_fence();
          wgmma_rs_n96(accg, a0[0], a0[1], a0[2], a0[3], db);
          wgmma_rs_n96(accu, a0[0], a0[1], a0[2], a0[3], db + 512);
          wgmma_rs_n96(accg, a1[0], a1[1], a1[2], a1[3], db + 128);
          wgmma_rs_n96(accu, a1[0], a1[1], a1[2], a1[3], db + 128 + 512);
          wg_commit();
          wg_wait<1>();
          if (kb > 0 && lane == 0) mbar_arrive(bars + 8 * (B_EMPTY + (st - 1) % 5));
        }
        {
          const int st = 17 + 2 * kb, slot = st % 5;
          ldsm4(a2, xb + (((4 + xhi) ^ xsw) << 4));
          ldsm4(a3, xb + (((6 + xhi) ^ xsw) << 4));
          mbar_wait(bars + 8 * (B_FULL + slot), (st / 5) & 1);
          const uint64_t db = mkdesc(sb + SM_RING + slot * 16384, 4096, 1024, 1);
          wg_fence();
          wgmma_rs_n96(accg, a2[0], a2[1], a2[2], a2[3], db);
          wgmma_rs_n96(accu, a2[0], a2[1], a2[2], a2[3], db + 512);
          wgmma_rs_n96(accg, a3[0], a3[1], a3[2], a3[3], db + 128);
          wgmma_rs_n96(accu, a3[0], a3[1], a3[2], a3[3], db + 128 + 512);
          wg_commit();
          wg_wait<1>();
          if (lane == 0) {
            mbar_arrive(bars + 8 * (B_EMPTY + (st - 1) % 5));
            if (kb == 3) mbar_arrive(bars + 8 * (B_XFREE + 3));
          }
        }
      }
      issue_half(accA, 0, H0{});
      wg_wait<1>();
      if (lane == 0) { mbar_arrive(bars + 8 * (B_EMPTY + 31 % 5)); mbar_arrive(bars + 8 * (B_XFREE + 7)); }
#pragma unroll
      for (int m = 0; m < 12; m++) {
        hf[32 + 2 * m] = hmul2_bf16(pack_bf16(accg[4 * m], accg[4 * m + 1]), pack_bf16(accu[4 * m], accu[4 * m + 1]));
        hf[32 + 2 * m + 1] = hmul2_bf16(pack_bf16(accg[4 * m + 2], accg[4 * m + 3]), pack_bf16(accu[4 * m + 2], accu[4 * m + 3]));
      }
    }
    auto send_pass = [&](float (&acc)[32], int s) {
      uint4* dst = (uint4*)(smem + SM_X + part_slot(s, wg) + (warp & 3) * 2048) + lane;
#pragma unroll
      for (int c = 0; c < 4; c++) {
        uint4 v;
        v.x = pack_bf16(acc[8 * c], acc[8 * c + 1]); v.y = pack_bf16(acc[8 * c + 2], acc[8 * c + 3]);
        v.z = pack_bf16(acc[8 * c + 4], acc[8 * c + 5]); v.w = pack_bf16(acc[8 * c + 6], acc[8 * c + 7]);
        dst[c * 32] = v;
      }
    };
    auto send_signal = [&](int s) {
      fence_async();
      __syncwarp();
      if (lane == 0) mbar_arrive(bars + 8 * (B_SENT + s));
    };
    auto part_load = [&](uint4 (&v)[4], int k) {
      const uint4* sp = g_part + (size_t)(((it_ * 8 + jf) * 8 + ((jf - k) & 7)) * 8 + warp) * 128 + lane;
#pragma unroll
      for (int c = 0; c < 4; c++) v[c] = ld_cg4(sp + c * 32);
    };
    auto part_add = [&](const uint4 (&v)[4]) {
#pragma unroll
      for (int c = 0; c < 4; c++) {
        accA[8 * c] += bf_lo(v[c].x); accA[8 * c + 1] += bf_hi(v[c].x); accA[8 * c + 2] += bf_lo(v[c].y); accA[8 * c + 3] += bf_hi(v[c].y);
        accA[8 * c + 4] += bf_lo(v[c].z); accA[8 * c + 5] += bf_hi(v[c].z); accA[8 * c + 6] += bf_lo(v[c].w); accA[8 * c + 7] += bf_hi(v[c].w);
      }
    };
    issue_half(accA, 0, H1{}); wg_wait<1>(); release(32);
    mbar_wait(bars + 8 * (B_XFREE + 7), 0);
    issue_half(accB, 1, H0{}); wg_wait<1>(); release(33); send_pass(accA, 0);
    issue_half(accB, 1, H1{}); send_signal(0); wg_wait<1>(); release(34);
    issue_half(accA, 2, H0{}); wg_wait<1>(); release(35); send_pass(accB, 1);
    issue_half(accA, 2, H1{}); send_signal(1); wg_wait<1>(); release(36);
    issue_half(accB, 3, H0{}); wg_wait<1>(); release(37); send_pass(accA, 2);
    issue_half(accB, 3, H1{}); send_signal(2); wg_wait<1>(); release(38);
    issue_half(accA, 4, H0{}); wg_wait<1>(); release(39); send_pass(accB, 3);
    issue_half(accA, 4, H1{}); send_signal(3); wg_wait<1>(); release(40);
    issue_half(accB, 5, H0{}); wg_wait<1>(); release(41); mbar_wait(bars + 8 * (B_STF + 0), 0); send_pass(accA, 4);
    issue_half(accB, 5, H1{}); send_signal(4); wg_wait<1>(); release(42);
    wg_wait<0>(); send_pass(accB, 5);
    {
      TM_IF(tid == 0, 10);
      const int w = warp & 3;
      mbar_wait(bars + 8 * B_RRDY, 0);
      TM_IF(tid == 0, 11);
      const uint32_t zero = lds32(sb + SM_X + CV_R + (2 * wg + 1) * R_CH + 128 * 16);
      const int c = tid & 127;
      const float* Sr = (const float*)(smem + SM_X + CV_S + wg * S_WG) + (127 - c);
      float* Sw = (float*)(smem + SM_X + CV_S + wg * S_WG) + w * 16 * S_PITCH + g * S_PITCH + 2 * q;
      uint32_t fa[4][4], fb[4][4];
      uint32_t ares[8] = {0, 0, 0, 0, 0, 0, 0, 0}, rv[8];
      auto load_u = [&](int ch) {
        const uint4 r0v = *(const uint4*)(smem + SM_X + CV_R + ch * R_CH + (127 - c) * 16);
        const uint4 r1v = *(const uint4*)(smem + SM_X + CV_R + ch * R_CH + R_HALF + (127 - c) * 16);
        rv[0] = r0v.x; rv[1] = r0v.y; rv[2] = r0v.z; rv[3] = r0v.w; rv[4] = r1v.x; rv[5] = r1v.y; rv[6] = r1v.z; rv[7] = r1v.w;
      };
#define POST(r2, dk2)                                                                              \
      {                                                                                            \
        float y_[2];                                                                               \
        _Pragma("unroll") for (int t2 = 0; t2 < 2; t2++) {                                         \
          const int r0 = 2 * (r2) + t2;                                                            \
          const float s1 = c >= 1 ? Sr[(16 + r0) * S_PITCH + 1] : 0.f;                             \
          const float s2 = c >= 2 ? Sr[(32 + r0) * S_PITCH + 2] : 0.f;                             \
          const float s3 = c >= 3 ? Sr[(48 + r0) * S_PITCH + 3] : 0.f;                             \
          y_[t2] = (Sr[r0 * S_PITCH] + s1) + (s2 + s3);                                            \
        }                                                                                          \
        ares[r2] = hadd2_bf16(pack_bf16(y_[0], y_[1]), hmul2_bf16(__byte_perm(rv[7 - (r2)], rv[7 - (r2)], 0x1032), dk2)); \
      }
      auto store_a = [&](int ch) {
        uint4* ap = (uint4*)(smem + SM_X + CV_R + ch * R_CH + c * 32);
        ap[0] = make_uint4(ares[0], ares[1], ares[2], ares[3]);
        ap[1] = make_uint4(ares[4], ares[5], ares[6], ares[7]);
        fence_async();
      };
      const uint32_t eoff = ((g & 1) ? E_COPY : 0) + (16 * w + (g & ~1) + 2 * q) * 2;
      const uint32_t dkA = dup_lo(dsk), dkB = dup_hi(dsk);
      {
        const int ch = 2 * wg;
        const uint32_t ebase = sb + SM_X + CV_E + ch * E_CH + eoff;
        const uint64_t de = mkdesc(sb + SM_X + CV_R + ch * R_CH, R_HALF, 128, 0);
        conv_load4<0>(fa, ebase, zero);
        conv_load4<4>(fb, ebase, zero);
        CONV_CHANNEL(mbar_wait(bars + 8 * (B_STF + 1), 0); mbar_wait(bars + 8 * (B_STF + 2), 0); mbar_wait(bars + 8 * (B_STF + 3), 0); mbar_wait(bars + 8 * (B_STF + 4), 0);, send_signal(5);, )
        TM_IF(tid == 0, 14);
      }
      issue_half(accA, 6, H0{});
      issue_half(accA, 6, H1{});
      bar_sync(6 + wg, 128);
      POST(0, dkA) POST(1, dkA) POST(2, dkA) POST(3, dkA) POST(4, dkA) POST(5, dkA) POST(6, dkA) POST(7, dkA)
      store_a(2 * wg);
      __syncwarp();
      if (lane == 0) mbar_arrive(bars + 8 * B_ADONE);
      {
        const int ch = 2 * wg + 1;
        const uint32_t ebase = sb + SM_X + CV_E + ch * E_CH + eoff;
        const uint64_t de = mkdesc(sb + SM_X + CV_R + ch * R_CH, R_HALF, 128, 0);
        conv_load4<0>(fa, ebase, zero);
        conv_load4<4>(fb, ebase, zero);
        wg_wait<0>();
        send_pass(accA, 6);
        CONV_CHANNEL(bar_sync(6 + wg, 128);, send_signal(6);, )
        bar_sync(6 + wg, 128);
        TM_IF(tid == 0, 17);
        POST(0, dkB) POST(1, dkB) POST(2, dkB) POST(3, dkB) POST(4, dkB) POST(5, dkB) POST(6, dkB) POST(7, dkB)
        store_a(ch);
        __syncwarp();
        if (lane == 0) mbar_arrive(bars + 8 * B_ADONE);
      }
#undef POST
    }
    {
      uint4 v0[4], v1[4], v2[4], v3[4];
      mbar_wait(bars + 8 * B_GOT, 0);
      part_load(v0, 1);
      part_load(v1, 2);
      part_load(v2, 3);
      part_load(v3, 4);
      issue_half(accB, 7, H0{});
      issue_half(accB, 7, H1{});
#pragma unroll
      for (int i = 0; i < 32; i++) accA[i] = 0.f;
      part_add(v0); part_load(v0, 5);
      part_add(v1); part_load(v1, 6);
      part_add(v2); part_load(v2, 7);
      part_add(v3);
      part_add(v0);
      part_add(v1);
      part_add(v2);
    }
    TM_IF(tid == 0, 28);
    mbar_wait(bars + 8 * B_ATILE, 0);
    TM_IF(tid == 0, 29);
    const int row0 = it_ * 128 + warp * 16 + g;
    const float g0 = __ldcg(g_gate + row0), g1 = __ldcg(g_gate + row0 + 8);
    uint32_t av[16];
    {
      const int dl = (lane & 7) + ((lane >> 4) << 3);
      const int chunk = 2 * (warp & 3) + ((lane >> 3) & 1);
      const uint32_t abase = sb + SM_AT + wg * 8192 + dl * 128 + ((chunk ^ (lane & 7)) << 4);
#pragma unroll
      for (int m2 = 0; m2 < 4; m2++) {
        asm volatile("ldmatrix.sync.aligned.m8n8.x4.trans.shared.b16 {%0,%1,%2,%3}, [%4];"
                     : "=r"(av[4 * m2]), "=r"(av[4 * m2 + 1]), "=r"(av[4 * m2 + 2]), "=r"(av[4 * m2 + 3]) : "r"(abase + m2 * 2048) : "memory");
      }
    }
    wg_wait<0>();
    const uint32_t gg0 = pack_bf16(g0, g0), gg1 = pack_bf16(g1, g1);
    const uint32_t og0 = pack_bf16(1.f - g0, 1.f - g0), og1 = pack_bf16(1.f - g1, 1.f - g1);
    uint32_t ov[16];
#pragma unroll
    for (int m = 0; m < 8; m++) {
      const uint32_t b0 = pack_bf16(accA[4 * m] + accB[4 * m], accA[4 * m + 1] + accB[4 * m + 1]);
      const uint32_t b1 = pack_bf16(accA[4 * m + 2] + accB[4 * m + 2], accA[4 * m + 3] + accB[4 * m + 3]);
      ov[2 * m] = hadd2_bf16(hmul2_bf16(gg0, av[2 * m]), hmul2_bf16(og0, b0));
      ov[2 * m + 1] = hadd2_bf16(hmul2_bf16(gg1, av[2 * m + 1]), hmul2_bf16(og1, b1));
    }
    {
      const uint32_t ob = sb + SM_X + CV_S + wg * S_WG + (warp & 3) * 2048;
      const int srow = (lane & 7) + ((lane >> 3) & 1) * 8;
#pragma unroll
      for (int m2 = 0; m2 < 4; m2++) {
        const int chunk = 2 * m2 + (lane >> 4);
        asm volatile("stmatrix.sync.aligned.m8n8.x4.shared.b16 [%0], {%1,%2,%3,%4};"
                     ::"r"(ob + srow * 128 + ((chunk ^ (srow & 7)) << 4)), "r"(ov[4 * m2]), "r"(ov[4 * m2 + 1]), "r"(ov[4 * m2 + 2]), "r"(ov[4 * m2 + 3]) : "memory");
      }
      __syncwarp();
#pragma unroll
      for (int i = 0; i < 4; i++) {
        const int r = 4 * i + (lane >> 3), chunk = lane & 7;
        const uint4 v = *(const uint4*)(smem + SM_X + CV_S + wg * S_WG + (warp & 3) * 2048 + r * 128 + ((chunk ^ (r & 7)) << 4));
        *(uint4*)(P.out + (it_ * 128 + warp * 16 + r) * D_ + jf * 64 + chunk * 8) = v;
      }
    }
    TM_IF(tid == 0, 30);
  }
}

typedef CUresult (*EncFn)(CUtensorMap*, CUtensorMapDataType, cuuint32_t, void*, const cuuint64_t*, const cuuint64_t*, const cuuint32_t*,
                          const cuuint32_t*, CUtensorMapInterleave, CUtensorMapSwizzle, CUtensorMapL2promotion, CUtensorMapFloatOOBfill);

struct HostState {
  bool ready;
  const void* key[4];
  Maps M;
};
HostState hs;

}

extern "C" void kernel_launch(void* const* d_in, const int* in_sizes, int n_in, void* d_out, int out_size) {
  (void)in_sizes; (void)n_in; (void)out_size;
  void* x = d_in[0];
  void* wg = d_in[8];
  void* wu = d_in[9];
  void* wd = d_in[10];
  if (!hs.ready || hs.key[0] != x || hs.key[1] != wg || hs.key[2] != wu || hs.key[3] != wd) {
    void* fn = nullptr;
    cudaDriverEntryPointQueryResult qr;
    cudaGetDriverEntryPoint("cuTensorMapEncodeTiled", &fn, cudaEnableDefault, &qr);
    EncFn enc = (EncFn)fn;
    const cuuint32_t es[3] = {1, 1, 1};
    const CUtensorMapDataType BF = CU_TENSOR_MAP_DATA_TYPE_BFLOAT16;
    const CUtensorMapInterleave IN = CU_TENSOR_MAP_INTERLEAVE_NONE;
    const CUtensorMapL2promotion PR = CU_TENSOR_MAP_L2_PROMOTION_L2_128B;
    const CUtensorMapFloatOOBfill OO = CU_TENSOR_MAP_FLOAT_OOB_FILL_NONE;
    {
      cuuint64_t gd[2] = {(cuuint64_t)D_, (cuuint64_t)L_}; cuuint64_t gs[1] = {(cuuint64_t)D_ * 2}; cuuint32_t box[2] = {64, 128};
      enc(&hs.M.X, BF, 2, x, gd, gs, box, es, IN, CU_TENSOR_MAP_SWIZZLE_128B, PR, OO);
    }
    {
      cuuint64_t gd[2] = {(cuuint64_t)F_, (cuuint64_t)D_}; cuuint64_t gs[1] = {(cuuint64_t)F_ * 2}; cuuint32_t box[2] = {64, 32};
      enc(&hs.M.Wg, BF, 2, wg, gd, gs, box, es, IN, CU_TENSOR_MAP_SWIZZLE_128B, PR, OO);
      enc(&hs.M.Wu, BF, 2, wu, gd, gs, box, es, IN, CU_TENSOR_MAP_SWIZZLE_128B, PR, OO);
      for (int o = 0; o < 2; o++) {
        cuuint64_t gd3[3] = {64, (cuuint64_t)D_, (cuuint64_t)(F_ / 64 - o)}; cuuint64_t gs3[2] = {(cuuint64_t)F_ * 2, 128};
        cuuint32_t box3[3] = {64, 32, 2};
        enc(&hs.M.Wg3[o], BF, 3, (char*)wg + 64 * o, gd3, gs3, box3, es, IN, CU_TENSOR_MAP_SWIZZLE_128B, PR, OO);
        enc(&hs.M.Wu3[o], BF, 3, (char*)wu + 64 * o, gd3, gs3, box3, es, IN, CU_TENSOR_MAP_SWIZZLE_128B, PR, OO);
      }
    }
    {
      cuuint64_t gd[2] = {(cuuint64_t)D_, (cuuint64_t)F_}; cuuint64_t gs[1] = {(cuuint64_t)D_ * 2}; cuuint32_t box[2] = {64, 112};
      enc(&hs.M.Wd, BF, 2, wd, gd, gs, box, es, IN, CU_TENSOR_MAP_SWIZZLE_128B, PR, OO);
    }
    {
      void* pa = nullptr;
      cudaGetSymbolAddress(&pa, g_aT);
      cuuint64_t gd[2] = {(cuuint64_t)L_, (cuuint64_t)D_}; cuuint64_t gs[1] = {(cuuint64_t)L_ * 2}; cuuint32_t box[2] = {64, 64};
      enc(&hs.M.AT, BF, 2, pa, gd, gs, box, es, IN, CU_TENSOR_MAP_SWIZZLE_128B, PR, OO);
    }
    cudaFuncSetAttribute(fused_kernel, cudaFuncAttributeMaxDynamicSharedMemorySize, SM_TOTAL);
    hs.key[0] = x; hs.key[1] = wg; hs.key[2] = wu; hs.key[3] = wd;
    hs.ready = true;
  }
  Params P;
  P.x = (const __nv_bfloat16*)d_in[0];
  P.log_A_real = (const __nv_bfloat16*)d_in[1];
  P.A_imag = (const __nv_bfloat16*)d_in[2];
  P.C_real = (const __nv_bfloat16*)d_in[3];
  P.C_imag = (const __nv_bfloat16*)d_in[4];
  P.log_dt = (const __nv_bfloat16*)d_in[5];
  P.D_skip = (const __nv_bfloat16*)d_in[6];
  P.gate_w = (const __nv_bfloat16*)d_in[11];
  P.w_gate = (const __nv_bfloat16*)wg;
  P.w_up = (const __nv_bfloat16*)wu;
  P.w_down = (const __nv_bfloat16*)wd;
  P.out = (__nv_bfloat16*)d_out;
  fused_kernel<<<NCTA, NTHREADS, SM_TOTAL>>>(hs.M, P);
}
```

```cpp
#include <cuda_runtime.h>
#include <cuda_bf16.h>
#include <cuda.h>
#include <stdint.h>

namespace {

constexpr int L_ = 2048, D_ = 512, F_ = 1792, NS_ = 128;
constexpr int NCTA = 128;
constexpr int NTHREADS = 384;

constexpr int SM_X = 0;
constexpr int SM_RING = 131072;
constexpr int KC_STRIDE = 656;
constexpr int SM_KB = 212992;
constexpr int SM_PR = SM_KB + 4 * KC_STRIDE * 2;
constexpr int SM_BAR = SM_PR + 512 * 24;
constexpr int SM_TOTAL = SM_BAR + 512;
constexpr int CV_R = 0;
constexpr int R_HALF = 156 * 16;
constexpr int R_CH = 2 * R_HALF;
constexpr int CV_E = 4 * R_CH;
constexpr int E_COPY = 4160;
constexpr int E_CH = 2 * E_COPY;
constexpr int CV_S = CV_E + 4 * E_CH;
constexpr int S_PITCH = 136;
constexpr int S_WG = 4 * 16 * S_PITCH * 4;
constexpr int SM_AT = SM_X;
static_assert(CV_S + 2 * S_WG + 8192 <= 131072, "conv region");
static_assert(SM_PR % 128 == 0, "alignment");

constexpr int B_FULL = 0, B_EMPTY = 5, B_XFULL = 10, B_XFREE = 18, B_ATILE = 26, B_RRDY = 27, B_ADONE = 28  , B_KSUM = 30, B_SENT = 35, B_GOT = 43, B_STF = 51;

__device__ uint4 g_part[16 * 8 * 8 * 8 * 4 * 32];
__device__ uint32_t g_flag[16 * 8 * 8];
__device__ __align__(1024) __nv_bfloat16 g_aT[D_ * L_];
__device__ float g_gate[L_];
__device__ uint32_t g_done1;
__device__ uint32_t g_cnt[8 * 32];
__device__ uint32_t g_exit;
__device__ uint32_t g_zero;
__device__ uint32_t g_epoch;

#define TM_IF(cond, idx) do {} while (0)
#define FAIL(a, ph) break
#define SPIN_LIMIT (1 << 22)
#define MBAR_LIMIT (1 << 20)
__device__ __forceinline__ uint32_t smem_u32(const void* p) { return (uint32_t)__cvta_generic_to_shared(p); }
__device__ __forceinline__ void mbar_init(uint32_t a, uint32_t c) { asm volatile("mbarrier.init.shared::cta.b64 [%0], %1;" ::"r"(a), "r"(c) : "memory"); }
__device__ __forceinline__ void mbar_expect(uint32_t a, uint32_t bytes) { asm volatile("mbarrier.arrive.expect_tx.shared::cta.b64 _, [%0], %1;" ::"r"(a), "r"(bytes) : "memory"); }
__device__ __forceinline__ void mbar_arrive(uint32_t a) { asm volatile("mbarrier.arrive.shared::cta.b64 _, [%0];" ::"r"(a) : "memory"); }
__device__ __forceinline__ void mbar_wait(uint32_t a, uint32_t ph) {
  asm volatile("{\n.reg .pred p;\n.reg .u32 c;\nmov.u32 c, 0;\nLW:\nmbarrier.try_wait.parity.shared::cta.b64 p, [%0], %1, %2;\n@p bra LD;\n"
               "add.u32 c, c, 1;\nsetp.lt.u32 p, c, 1048576;\n@p bra LW;\nLD:\n}" ::"r"(a), "r"(ph), "r"(20000u) : "memory");
}
template <int NS> __device__ __forceinline__ void mbar_wait_lazy(uint32_t a, uint32_t ph) {
  asm volatile("{\n.reg .pred p;\n.reg .u32 c;\nmov.u32 c, 0;\nLW:\nmbarrier.test_wait.parity.shared::cta.b64 p, [%0], %1;\n@p bra LD;\n"
               "nanosleep.u32 %2;\nadd.u32 c, c, 1;\nsetp.lt.u32 p, c, 4194304;\n@p bra LW;\nLD:\n}" ::"r"(a), "r"(ph), "n"(NS) : "memory");
}
__device__ __forceinline__ void tma2d(uint32_t dst, const CUtensorMap* m, int c0, int c1, uint32_t bar) {
  asm volatile("cp.async.bulk.tensor.2d.shared::cluster.global.mbarrier::complete_tx::bytes [%0], [%1, {%3,%4}], [%2];" ::"r"(dst), "l"(m), "r"(bar), "r"(c0), "r"(c1) : "memory");
}
__device__ __forceinline__ void tma3d(uint32_t dst, const CUtensorMap* m, int c0, int c1, int c2, uint32_t bar) {
  asm volatile("cp.async.bulk.tensor.3d.shared::cluster.global.mbarrier::complete_tx::bytes [%0], [%1, {%3,%4,%5}], [%2];" ::"r"(dst), "l"(m), "r"(bar), "r"(c0), "r"(c1), "r"(c2) : "memory");
}
__device__ __forceinline__ uint64_t mkdesc(uint32_t addr, uint32_t lbo, uint32_t sbo, uint32_t sw) {
  return (uint64_t)((addr & 0x3FFFF) >> 4) | ((uint64_t)(lbo >> 4) << 16) | ((uint64_t)(sbo >> 4) << 32) | ((uint64_t)sw << 62);
}
__device__ __forceinline__ void wg_fence() { asm volatile("wgmma.fence.sync.aligned;" ::: "memory"); }
__device__ __forceinline__ void wg_commit() { asm volatile("wgmma.commit_group.sync.aligned;" ::: "memory"); }
template <int N> __device__ __forceinline__ void wg_wait() { asm volatile("wgmma.wait_group.sync.aligned %0;" ::"n"(N) : "memory"); }
__device__ __forceinline__ void zero_reg(float& x) { asm volatile("mov.f32 %0, 0f00000000;" : "=f"(x)); }
__device__ __forceinline__ void movf(float& d, float s) { asm volatile("mov.f32 %0, %1;" : "=f"(d) : "f"(s)); }
__device__ __forceinline__ void bar_sync(int id, int n) { asm volatile("bar.sync %0, %1;" ::"r"(id), "r"(n) : "memory"); }
__device__ __forceinline__ void fence_async() { asm volatile("fence.proxy.async.shared::cta;" ::: "memory"); }
__device__ __forceinline__ uint32_t pack_bf16(float lo, float hi) {
  uint32_t r;
  asm("cvt.rn.bf16x2.f32 %0, %1, %2;" : "=r"(r) : "f"(hi), "f"(lo));
  return r;
}
__device__ __forceinline__ uint32_t hmul2_bf16(uint32_t a, uint32_t b) {
  uint32_t r;
  asm("mul.rn.bf16x2 %0, %1, %2;" : "=r"(r) : "r"(a), "r"(b));
  return r;
}
__device__ __forceinline__ uint32_t hadd2_bf16(uint32_t a, uint32_t b) {
  uint32_t r;
  asm("add.rn.bf16x2 %0, %1, %2;" : "=r"(r) : "r"(a), "r"(b));
  return r;
}
__device__ __forceinline__ float bf_lo(uint32_t v) { return __uint_as_float(v << 16); }
__device__ __forceinline__ float bf_hi(uint32_t v) { return __uint_as_float(v & 0xFFFF0000u); }
__device__ __forceinline__ float bf16r(float x) { return __bfloat162float(__float2bfloat16_rn(x)); }
__device__ __forceinline__ float ldbf(const __nv_bfloat16* p) { return __bfloat162float(*p); }
__device__ __forceinline__ uint32_t ld_acquire(const uint32_t* p) {
  uint32_t v;
  asm volatile("ld.acquire.gpu.global.u32 %0, [%1];" : "=r"(v) : "l"(p) : "memory");
  return v;
}
__device__ __forceinline__ void st_release(uint32_t* p, uint32_t v) { asm volatile("st.release.gpu.global.u32 [%0], %1;" ::"l"(p), "r"(v) : "memory"); }
__device__ __forceinline__ uint4 ld_cg4(const uint4* p) {
  uint4 v;
  asm volatile("ld.global.cg.v4.u32 {%0,%1,%2,%3}, [%4];" : "=r"(v.x), "=r"(v.y), "=r"(v.z), "=r"(v.w) : "l"(p) : "memory");
  return v;
}
__device__ __forceinline__ uint32_t ld_cg1(const void* p) {
  uint32_t v;
  asm volatile("ld.global.cg.u32 %0, [%1];" : "=r"(v) : "l"(p) : "memory");
  return v;
}
__device__ __forceinline__ uint32_t lds32(uint32_t a) {
  uint32_t v;
  asm volatile("ld.shared.u32 %0, [%1];" : "=r"(v) : "r"(a) : "memory");
  return v;
}
__device__ __forceinline__ void ldsm4(uint32_t (&r)[4], uint32_t a) {
  asm volatile("ldmatrix.sync.aligned.m8n8.x4.shared.b16 {%0,%1,%2,%3}, [%4];" : "=r"(r[0]), "=r"(r[1]), "=r"(r[2]), "=r"(r[3]) : "r"(a) : "memory");
}
__device__ __forceinline__ uint32_t pack_f16(float lo, float hi) {
  uint32_t r;
  asm("cvt.rn.f16x2.f32 %0, %1, %2;" : "=r"(r) : "f"(hi), "f"(lo));
  return r;
}

__device__ __forceinline__ void wgmma_ss_n256(float (&d)[128], uint64_t da, uint64_t db) {
  asm volatile("wgmma.mma_async.sync.aligned.m64n256k16.f32.bf16.bf16 {%0, %1, %2, %3, %4, %5, %6, %7, %8, %9, %10, %11, %12, %13, %14, %15, %16, %17, %18, %19, %20, %21, %22, %23, %24, %25, %26, %27, %28, %29, %30, %31, %32, %33, %34, %35, %36, %37, %38, %39, %40, %41, %42, %43, %44, %45, %46, %47, %48, %49, %50, %51, %52, %53, %54, %55, %56, %57, %58, %59, %60, %61, %62, %63, %64, %65, %66, %67, %68, %69, %70, %71, %72, %73, %74, %75, %76, %77, %78, %79, %80, %81, %82, %83, %84, %85, %86, %87, %88, %89, %90, %91, %92, %93, %94, %95, %96, %97, %98, %99, %100, %101, %102, %103, %104, %105, %106, %107, %108, %109, %110, %111, %112, %113, %114, %115, %116, %117, %118, %119, %120, %121, %122, %123, %124, %125, %126, %127}, %128, %129, 1, 1, 1, 0, 1;"
    : "+f"(d[0]), "+f"(d[1]), "+f"(d[2]), "+f"(d[3]), "+f"(d[4]), "+f"(d[5]), "+f"(d[6]), "+f"(d[7]), "+f"(d[8]), "+f"(d[9]), "+f"(d[10]), "+f"(d[11]), "+f"(d[12]), "+f"(d[13]), "+f"(d[14]), "+f"(d[15]), "+f"(d[16]), "+f"(d[17]), "+f"(d[18]), "+f"(d[19]), "+f"(d[20]), "+f"(d[21]), "+f"(d[22]), "+f"(d[23]), "+f"(d[24]), "+f"(d[25]), "+f"(d[26]), "+f"(d[27]), "+f"(d[28]), "+f"(d[29]), "+f"(d[30]), "+f"(d[31]), "+f"(d[32]), "+f"(d[33]), "+f"(d[34]), "+f"(d[35]), "+f"(d[36]), "+f"(d[37]), "+f"(d[38]), "+f"(d[39]), "+f"(d[40]), "+f"(d[41]), "+f"(d[42]), "+f"(d[43]), "+f"(d[44]), "+f"(d[45]), "+f"(d[46]), "+f"(d[47]), "+f"(d[48]), "+f"(d[49]), "+f"(d[50]), "+f"(d[51]), "+f"(d[52]), "+f"(d[53]), "+f"(d[54]), "+f"(d[55]), "+f"(d[56]), "+f"(d[57]), "+f"(d[58]), "+f"(d[59]), "+f"(d[60]), "+f"(d[61]), "+f"(d[62]), "+f"(d[63]), "+f"(d[64]), "+f"(d[65]), "+f"(d[66]), "+f"(d[67]), "+f"(d[68]), "+f"(d[69]), "+f"(d[70]), "+f"(d[71]), "+f"(d[72]), "+f"(d[73]), "+f"(d[74]), "+f"(d[75]), "+f"(d[76]), "+f"(d[77]), "+f"(d[78]), "+f"(d[79]), "+f"(d[80]), "+f"(d[81]), "+f"(d[82]), "+f"(d[83]), "+f"(d[84]), "+f"(d[85]), "+f"(d[86]), "+f"(d[87]), "+f"(d[88]), "+f"(d[89]), "+f"(d[90]), "+f"(d[91]), "+f"(d[92]), "+f"(d[93]), "+f"(d[94]), "+f"(d[95]), "+f"(d[96]), "+f"(d[97]), "+f"(d[98]), "+f"(d[99]), "+f"(d[100]), "+f"(d[101]), "+f"(d[102]), "+f"(d[103]), "+f"(d[104]), "+f"(d[105]), "+f"(d[106]), "+f"(d[107]), "+f"(d[108]), "+f"(d[109]), "+f"(d[110]), "+f"(d[111]), "+f"(d[112]), "+f"(d[113]), "+f"(d[114]), "+f"(d[115]), "+f"(d[116]), "+f"(d[117]), "+f"(d[118]), "+f"(d[119]), "+f"(d[120]), "+f"(d[121]), "+f"(d[122]), "+f"(d[123]), "+f"(d[124]), "+f"(d[125]), "+f"(d[126]), "+f"(d[127]) : "l"(da), "l"(db));
}
__device__ __forceinline__ void wgmma_rs_n96(float (&d)[48], uint32_t a0, uint32_t a1, uint32_t a2, uint32_t a3, uint64_t db) {
  asm volatile("wgmma.mma_async.sync.aligned.m64n96k16.f32.bf16.bf16 {%0, %1, %2, %3, %4, %5, %6, %7, %8, %9, %10, %11, %12, %13, %14, %15, %16, %17, %18, %19, %20, %21, %22, %23, %24, %25, %26, %27, %28, %29, %30, %31, %32, %33, %34, %35, %36, %37, %38, %39, %40, %41, %42, %43, %44, %45, %46, %47}, {%48,%49,%50,%51}, %52, 1, 1, 1, 1;"
    : "+f"(d[0]), "+f"(d[1]), "+f"(d[2]), "+f"(d[3]), "+f"(d[4]), "+f"(d[5]), "+f"(d[6]), "+f"(d[7]), "+f"(d[8]), "+f"(d[9]), "+f"(d[10]), "+f"(d[11]), "+f"(d[12]), "+f"(d[13]), "+f"(d[14]), "+f"(d[15]), "+f"(d[16]), "+f"(d[17]), "+f"(d[18]), "+f"(d[19]), "+f"(d[20]), "+f"(d[21]), "+f"(d[22]), "+f"(d[23]), "+f"(d[24]), "+f"(d[25]), "+f"(d[26]), "+f"(d[27]), "+f"(d[28]), "+f"(d[29]), "+f"(d[30]), "+f"(d[31]), "+f"(d[32]), "+f"(d[33]), "+f"(d[34]), "+f"(d[35]), "+f"(d[36]), "+f"(d[37]), "+f"(d[38]), "+f"(d[39]), "+f"(d[40]), "+f"(d[41]), "+f"(d[42]), "+f"(d[43]), "+f"(d[44]), "+f"(d[45]), "+f"(d[46]), "+f"(d[47]) : "r"(a0), "r"(a1), "r"(a2), "r"(a3), "l"(db));
}
__device__ __forceinline__ void wgmma_rs_n64t(float (&d)[32], uint32_t a0, uint32_t a1, uint32_t a2, uint32_t a3, uint64_t db) {
  asm volatile("wgmma.mma_async.sync.aligned.m64n64k16.f32.bf16.bf16 {%0, %1, %2, %3, %4, %5, %6, %7, %8, %9, %10, %11, %12, %13, %14, %15, %16, %17, %18, %19, %20, %21, %22, %23, %24, %25, %26, %27, %28, %29, %30, %31}, {%32,%33,%34,%35}, %36, 1, 1, 1, 1;"
    : "+f"(d[0]), "+f"(d[1]), "+f"(d[2]), "+f"(d[3]), "+f"(d[4]), "+f"(d[5]), "+f"(d[6]), "+f"(d[7]), "+f"(d[8]), "+f"(d[9]), "+f"(d[10]), "+f"(d[11]), "+f"(d[12]), "+f"(d[13]), "+f"(d[14]), "+f"(d[15]), "+f"(d[16]), "+f"(d[17]), "+f"(d[18]), "+f"(d[19]), "+f"(d[20]), "+f"(d[21]), "+f"(d[22]), "+f"(d[23]), "+f"(d[24]), "+f"(d[25]), "+f"(d[26]), "+f"(d[27]), "+f"(d[28]), "+f"(d[29]), "+f"(d[30]), "+f"(d[31]) : "r"(a0), "r"(a1), "r"(a2), "r"(a3), "l"(db));
}
__device__ __forceinline__ void cw128z(float (&d)[64], uint32_t a0, uint32_t a1, uint32_t a2, uint32_t a3, uint64_t db) {
  asm volatile("{.reg .pred p; setp.ne.b32 p, 0, 0; wgmma.mma_async.sync.aligned.m64n128k16.f32.bf16.bf16 {%0, %1, %2, %3, %4, %5, %6, %7, %8, %9, %10, %11, %12, %13, %14, %15, %16, %17, %18, %19, %20, %21, %22, %23, %24, %25, %26, %27, %28, %29, %30, %31, %32, %33, %34, %35, %36, %37, %38, %39, %40, %41, %42, %43, %44, %45, %46, %47, %48, %49, %50, %51, %52, %53, %54, %55, %56, %57, %58, %59, %60, %61, %62, %63}, {%64,%65,%66,%67}, %68, p, 1, 1, 0;}"
    : "=f"(d[0]), "=f"(d[1]), "=f"(d[2]), "=f"(d[3]), "=f"(d[4]), "=f"(d[5]), "=f"(d[6]), "=f"(d[7]), "=f"(d[8]), "=f"(d[9]), "=f"(d[10]), "=f"(d[11]), "=f"(d[12]), "=f"(d[13]), "=f"(d[14]), "=f"(d[15]), "=f"(d[16]), "=f"(d[17]), "=f"(d[18]), "=f"(d[19]), "=f"(d[20]), "=f"(d[21]), "=f"(d[22]), "=f"(d[23]), "=f"(d[24]), "=f"(d[25]), "=f"(d[26]), "=f"(d[27]), "=f"(d[28]), "=f"(d[29]), "=f"(d[30]), "=f"(d[31]), "=f"(d[32]), "=f"(d[33]), "=f"(d[34]), "=f"(d[35]), "=f"(d[36]), "=f"(d[37]), "=f"(d[38]), "=f"(d[39]), "=f"(d[40]), "=f"(d[41]), "=f"(d[42]), "=f"(d[43]), "=f"(d[44]), "=f"(d[45]), "=f"(d[46]), "=f"(d[47]), "=f"(d[48]), "=f"(d[49]), "=f"(d[50]), "=f"(d[51]), "=f"(d[52]), "=f"(d[53]), "=f"(d[54]), "=f"(d[55]), "=f"(d[56]), "=f"(d[57]), "=f"(d[58]), "=f"(d[59]), "=f"(d[60]), "=f"(d[61]), "=f"(d[62]), "=f"(d[63]) : "r"(a0), "r"(a1), "r"(a2), "r"(a3), "l"(db));
}
__device__ __forceinline__ void cw128(float (&d)[64], uint32_t a0, uint32_t a1, uint32_t a2, uint32_t a3, uint64_t db) {
  asm volatile("wgmma.mma_async.sync.aligned.m64n128k16.f32.bf16.bf16 {%0, %1, %2, %3, %4, %5, %6, %7, %8, %9, %10, %11, %12, %13, %14, %15, %16, %17, %18, %19, %20, %21, %22, %23, %24, %25, %26, %27, %28, %29, %30, %31, %32, %33, %34, %35, %36, %37, %38, %39, %40, %41, %42, %43, %44, %45, %46, %47, %48, %49, %50, %51, %52, %53, %54, %55, %56, %57, %58, %59, %60, %61, %62, %63}, {%64,%65,%66,%67}, %68, 1, 1, 1, 0;"
    : "+f"(d[0]), "+f"(d[1]), "+f"(d[2]), "+f"(d[3]), "+f"(d[4]), "+f"(d[5]), "+f"(d[6]), "+f"(d[7]), "+f"(d[8]), "+f"(d[9]), "+f"(d[10]), "+f"(d[11]), "+f"(d[12]), "+f"(d[13]), "+f"(d[14]), "+f"(d[15]), "+f"(d[16]), "+f"(d[17]), "+f"(d[18]), "+f"(d[19]), "+f"(d[20]), "+f"(d[21]), "+f"(d[22]), "+f"(d[23]), "+f"(d[24]), "+f"(d[25]), "+f"(d[26]), "+f"(d[27]), "+f"(d[28]), "+f"(d[29]), "+f"(d[30]), "+f"(d[31]), "+f"(d[32]), "+f"(d[33]), "+f"(d[34]), "+f"(d[35]), "+f"(d[36]), "+f"(d[37]), "+f"(d[38]), "+f"(d[39]), "+f"(d[40]), "+f"(d[41]), "+f"(d[42]), "+f"(d[43]), "+f"(d[44]), "+f"(d[45]), "+f"(d[46]), "+f"(d[47]), "+f"(d[48]), "+f"(d[49]), "+f"(d[50]), "+f"(d[51]), "+f"(d[52]), "+f"(d[53]), "+f"(d[54]), "+f"(d[55]), "+f"(d[56]), "+f"(d[57]), "+f"(d[58]), "+f"(d[59]), "+f"(d[60]), "+f"(d[61]), "+f"(d[62]), "+f"(d[63]) : "r"(a0), "r"(a1), "r"(a2), "r"(a3), "l"(db));
}
__device__ __forceinline__ void cw96(float (&d)[48], uint32_t a0, uint32_t a1, uint32_t a2, uint32_t a3, uint64_t db) {
  asm volatile("wgmma.mma_async.sync.aligned.m64n96k16.f32.bf16.bf16 {%0, %1, %2, %3, %4, %5, %6, %7, %8, %9, %10, %11, %12, %13, %14, %15, %16, %17, %18, %19, %20, %21, %22, %23, %24, %25, %26, %27, %28, %29, %30, %31, %32, %33, %34, %35, %36, %37, %38, %39, %40, %41, %42, %43, %44, %45, %46, %47}, {%48,%49,%50,%51}, %52, 1, 1, 1, 0;"
    : "+f"(d[0]), "+f"(d[1]), "+f"(d[2]), "+f"(d[3]), "+f"(d[4]), "+f"(d[5]), "+f"(d[6]), "+f"(d[7]), "+f"(d[8]), "+f"(d[9]), "+f"(d[10]), "+f"(d[11]), "+f"(d[12]), "+f"(d[13]), "+f"(d[14]), "+f"(d[15]), "+f"(d[16]), "+f"(d[17]), "+f"(d[18]), "+f"(d[19]), "+f"(d[20]), "+f"(d[21]), "+f"(d[22]), "+f"(d[23]), "+f"(d[24]), "+f"(d[25]), "+f"(d[26]), "+f"(d[27]), "+f"(d[28]), "+f"(d[29]), "+f"(d[30]), "+f"(d[31]), "+f"(d[32]), "+f"(d[33]), "+f"(d[34]), "+f"(d[35]), "+f"(d[36]), "+f"(d[37]), "+f"(d[38]), "+f"(d[39]), "+f"(d[40]), "+f"(d[41]), "+f"(d[42]), "+f"(d[43]), "+f"(d[44]), "+f"(d[45]), "+f"(d[46]), "+f"(d[47]) : "r"(a0), "r"(a1), "r"(a2), "r"(a3), "l"(db));
}
__device__ __forceinline__ void cw64(float (&d)[32], uint32_t a0, uint32_t a1, uint32_t a2, uint32_t a3, uint64_t db) {
  asm volatile("wgmma.mma_async.sync.aligned.m64n64k16.f32.bf16.bf16 {%0, %1, %2, %3, %4, %5, %6, %7, %8, %9, %10, %11, %12, %13, %14, %15, %16, %17, %18, %19, %20, %21, %22, %23, %24, %25, %26, %27, %28, %29, %30, %31}, {%32,%33,%34,%35}, %36, 1, 1, 1, 0;"
    : "+f"(d[0]), "+f"(d[1]), "+f"(d[2]), "+f"(d[3]), "+f"(d[4]), "+f"(d[5]), "+f"(d[6]), "+f"(d[7]), "+f"(d[8]), "+f"(d[9]), "+f"(d[10]), "+f"(d[11]), "+f"(d[12]), "+f"(d[13]), "+f"(d[14]), "+f"(d[15]), "+f"(d[16]), "+f"(d[17]), "+f"(d[18]), "+f"(d[19]), "+f"(d[20]), "+f"(d[21]), "+f"(d[22]), "+f"(d[23]), "+f"(d[24]), "+f"(d[25]), "+f"(d[26]), "+f"(d[27]), "+f"(d[28]), "+f"(d[29]), "+f"(d[30]), "+f"(d[31]) : "r"(a0), "r"(a1), "r"(a2), "r"(a3), "l"(db));
}
__device__ __forceinline__ void cw32(float (&d)[16], uint32_t a0, uint32_t a1, uint32_t a2, uint32_t a3, uint64_t db) {
  asm volatile("wgmma.mma_async.sync.aligned.m64n32k16.f32.bf16.bf16 {%0, %1, %2, %3, %4, %5, %6, %7, %8, %9, %10, %11, %12, %13, %14, %15}, {%16,%17,%18,%19}, %20, 1, 1, 1, 0;"
    : "+f"(d[0]), "+f"(d[1]), "+f"(d[2]), "+f"(d[3]), "+f"(d[4]), "+f"(d[5]), "+f"(d[6]), "+f"(d[7]), "+f"(d[8]), "+f"(d[9]), "+f"(d[10]), "+f"(d[11]), "+f"(d[12]), "+f"(d[13]), "+f"(d[14]), "+f"(d[15]) : "r"(a0), "r"(a1), "r"(a2), "r"(a3), "l"(db));
}

struct cpx { float r, i; };
__device__ __forceinline__ cpx cmul(cpx a, cpx b) { return {fmaf(a.r, b.r, -a.i * b.i), fmaf(a.r, b.i, a.i * b.r)}; }
__device__ __forceinline__ cpx csqr(cpx a) { return {fmaf(a.r, a.r, -a.i * a.i), (a.r * a.i) * 2.f}; }
__device__ __forceinline__ cpx cmulc(cpx a, cpx b) { return {fmaf(a.r, b.r, -a.i * b.i), fmaf(-a.r, b.i, -a.i * b.r)}; }
__device__ __forceinline__ cpx cexp_fast(float re, float im) {
  float e;
  asm("ex2.approx.ftz.f32 %0, %1;" : "=f"(e) : "f"(re * 1.4426950408889634f));
  float k = rintf(im * 0.15915494309189535f);
  float r = fmaf(k, -6.2831854820251465f, im);
  r = fmaf(k, 1.7484555314695172e-07f, r);
  float s, c;
  asm("sin.approx.f32 %0, %1;" : "=f"(s) : "f"(r));
  asm("cos.approx.f32 %0, %1;" : "=f"(c) : "f"(r));
  return {e * c, e * s};
}

struct KOps { uint32_t xa[5], xb[5], y[4]; };
__device__ __forceinline__ void kgen_ops(KOps& o, const float4 pr, const float2 qq, const float gf) {
  const cpx C = {pr.z, pr.w};
  const cpx Q = {qq.x, qq.y};
  const cpx V0 = cexp_fast(pr.x * gf, pr.y * gf);
  const cpx V1 = csqr(V0), V2 = csqr(V1), V3 = csqr(V2);
  const cpx Y0 = cmulc(C, V0), Y1 = cmulc(C, V1), Y2 = cmulc(C, V2), Y3 = cmulc(C, V3);
  o.y[0] = pack_f16(Y0.r, Y0.i); o.y[1] = pack_f16(Y1.r, Y1.i); o.y[2] = pack_f16(Y2.r, Y2.i); o.y[3] = pack_f16(Y3.r, Y3.i);
  const cpx Xb = cmul(V3, Q);
  cpx Xc = cmul(Xb, Q), Xd = cmul(Xc, Q);
  o.xa[0] = pack_f16(V3.r, V3.i); o.xb[0] = pack_f16(Xb.r, Xb.i);
  o.xa[1] = pack_f16(Xc.r, Xc.i); o.xb[1] = pack_f16(Xd.r, Xd.i);
#pragma unroll
  for (int k = 2; k < 5; k++) {
    Xc = csqr(Xc); Xd = csqr(Xd);
    o.xa[k] = pack_f16(Xc.r, Xc.i); o.xb[k] = pack_f16(Xd.r, Xd.i);
  }
}
__device__ __forceinline__ void kgen_mma(float (&T)[5][4], const KOps& a, const KOps& b) {
  asm("mma.sync.aligned.m16n8k16.row.col.f32.f16.f16.f32 {%0,%1,%2,%3}, {%20,%21,%22,%23}, {%40,%41}, {%0,%1,%2,%3};\n"
      "mma.sync.aligned.m16n8k16.row.col.f32.f16.f16.f32 {%4,%5,%6,%7}, {%24,%25,%26,%27}, {%40,%41}, {%4,%5,%6,%7};\n"
      "mma.sync.aligned.m16n8k16.row.col.f32.f16.f16.f32 {%8,%9,%10,%11}, {%28,%29,%30,%31}, {%42,%43}, {%8,%9,%10,%11};\n"
      "mma.sync.aligned.m16n8k16.row.col.f32.f16.f16.f32 {%12,%13,%14,%15}, {%32,%33,%34,%35}, {%44,%45}, {%12,%13,%14,%15};\n"
      "mma.sync.aligned.m16n8k16.row.col.f32.f16.f16.f32 {%16,%17,%18,%19}, {%36,%37,%38,%39}, {%46,%47}, {%16,%17,%18,%19};\n"
      : "+f"(T[0][0]), "+f"(T[0][1]), "+f"(T[0][2]), "+f"(T[0][3]), "+f"(T[1][0]), "+f"(T[1][1]), "+f"(T[1][2]), "+f"(T[1][3]),
        "+f"(T[2][0]), "+f"(T[2][1]), "+f"(T[2][2]), "+f"(T[2][3]), "+f"(T[3][0]), "+f"(T[3][1]), "+f"(T[3][2]), "+f"(T[3][3]),
        "+f"(T[4][0]), "+f"(T[4][1]), "+f"(T[4][2]), "+f"(T[4][3])
      : "r"(a.xa[0]), "r"(a.xb[0]), "r"(b.xa[0]), "r"(b.xb[0]), "r"(a.xa[1]), "r"(a.xb[1]), "r"(b.xa[1]), "r"(b.xb[1]),
        "r"(a.xa[2]), "r"(a.xb[2]), "r"(b.xa[2]), "r"(b.xb[2]), "r"(a.xa[3]), "r"(a.xb[3]), "r"(b.xa[3]), "r"(b.xb[3]),
        "r"(a.xa[4]), "r"(a.xb[4]), "r"(b.xa[4]), "r"(b.xb[4]),
        "r"(a.y[0]), "r"(b.y[0]), "r"(a.y[1]), "r"(b.y[1]), "r"(a.y[2]), "r"(b.y[2]), "r"(a.y[3]), "r"(b.y[3]));
}

template <int J0> __device__ __forceinline__ void conv_load4(uint32_t (&f)[4][4], uint32_t ebase, uint32_t zero) {
#pragma unroll
  for (int t = 0; t < 4; t++) {
    f[t][0] = lds32(ebase + (J0 + t) * 128);
    f[t][1] = lds32(ebase + (J0 + t) * 128 + 16);
    f[t][3] = lds32(ebase + (J0 + t) * 128 + 32);
  }
#pragma unroll
  for (int t = 0; t < 4; t++)
    asm volatile("xor.b32 %0, %1, %2;" : "=r"(f[t][2]) : "r"(f[t][1]), "r"(zero));
}
#define CONV_GRP(FN, ACC, J0, F)                                                             \
  wg_fence();                                                                                \
  FN(ACC, F[0][0], F[0][1], F[0][2], F[0][3], de + 4 * (J0));                                \
  FN(ACC, F[1][0], F[1][1], F[1][2], F[1][3], de + 4 * (J0 + 1));                            \
  FN(ACC, F[2][0], F[2][1], F[2][2], F[2][3], de + 4 * (J0 + 2));                            \
  FN(ACC, F[3][0], F[3][1], F[3][2], F[3][3], de + 4 * (J0 + 3));                            \
  wg_commit();
#define CONV_STAGE(ACC, M0)                                                                  \
  _Pragma("unroll") for (int m = (M0); m < (M0) + 4; m++) {                                  \
    *(float2*)(Sw + 8 * m) = make_float2(ACC[4 * m], ACC[4 * m + 1]);                        \
    *(float2*)(Sw + 8 * S_PITCH + 8 * m) = make_float2(ACC[4 * m + 2], ACC[4 * m + 3]);      \
  }
#define CONV_CHANNEL(PRE, MID1, MID2)                                                                    \
  {                                                                                          \
    float a128[64], a96[48], a64[32], a32[16];                                               \
    wg_fence();                                                                              \
    cw128z(a128, fa[0][0], fa[0][1], fa[0][2], fa[0][3], de);                                \
    cw128(a128, fa[1][0], fa[1][1], fa[1][2], fa[1][3], de + 4);                             \
    cw128(a128, fa[2][0], fa[2][1], fa[2][2], fa[2][3], de + 8);                             \
    cw128(a128, fa[3][0], fa[3][1], fa[3][2], fa[3][3], de + 12);                            \
    wg_commit();                                                                             \
    CONV_GRP(cw128, a128, 4, fb)                                                             \
    MID1                                                                                     \
    wg_wait<1>(); conv_load4<8>(fa, ebase, zero);                                            \
    wg_wait<0>(); conv_load4<12>(fb, ebase, zero);                                           \
    _Pragma("unroll") for (int i = 0; i < 48; i++) movf(a96[i], a128[i]);                       \
    CONV_GRP(cw96, a96, 8, fa)                                                               \
    CONV_GRP(cw96, a96, 12, fb)                                                              \
    MID2                                                                                     \
    PRE                                                                                      \
    CONV_STAGE(a128, 12)                                                                     \
    wg_wait<1>(); conv_load4<16>(fa, ebase, zero);                                           \
    wg_wait<0>(); conv_load4<20>(fb, ebase, zero);                                           \
    _Pragma("unroll") for (int i = 0; i < 32; i++) movf(a64[i], a96[i]);                        \
    CONV_GRP(cw64, a64, 16, fa)                                                              \
    CONV_GRP(cw64, a64, 20, fb)                                                              \
    CONV_STAGE(a96, 8)                                                                       \
    wg_wait<1>(); conv_load4<24>(fa, ebase, zero);                                           \
    wg_wait<0>(); conv_load4<28>(fb, ebase, zero);                                           \
    _Pragma("unroll") for (int i = 0; i < 16; i++) movf(a32[i], a64[i]);                        \
    CONV_GRP(cw32, a32, 24, fa)                                                              \
    CONV_GRP(cw32, a32, 28, fb)                                                              \
    CONV_STAGE(a64, 4)                                                                       \
    load_u(ch);                                                                              \
    wg_wait<0>();                                                                            \
    CONV_STAGE(a32, 0)                                                                       \
  }

__device__ __forceinline__ int part_slot(int s, int v) {
  if (s == 6) return CV_E + 2 * v * E_CH;
  if (s == 5) return v ? (SM_PR - SM_X) : (CV_S + 2 * S_WG);
  return CV_S + v * S_WG + (s & 3) * 8192;
}
template <int V> struct IC { static constexpr int value = V; };

struct Params {
  const __nv_bfloat16* x;
  const __nv_bfloat16* log_A_real;
  const __nv_bfloat16* A_imag;
  const __nv_bfloat16* C_real;
  const __nv_bfloat16* C_imag;
  const __nv_bfloat16* log_dt;
  const __nv_bfloat16* D_skip;
  const __nv_bfloat16* gate_w;
  const __nv_bfloat16* w_gate;
  const __nv_bfloat16* w_up;
  const __nv_bfloat16* w_down;
  __nv_bfloat16* out;
};

struct Maps {
  CUtensorMap X, Wg, Wu, Wg3[2], Wu3[2], Wd, AT;
};

__device__ __forceinline__ uint32_t ld_epoch() { return *(volatile uint32_t*)&g_epoch; }
__device__ __forceinline__ uint32_t dup_lo(uint32_t w) { return __byte_perm(w, w, 0x1010); }
__device__ __forceinline__ uint32_t dup_hi(uint32_t w) { return __byte_perm(w, w, 0x3232); }

__global__ void __launch_bounds__(NTHREADS, 1)
fused_kernel(const __grid_constant__ Maps M, const Params P) {
  extern __shared__ __align__(1024) uint8_t smem[];
  const uint32_t sb = smem_u32(smem);
  const uint32_t bars = sb + SM_BAR;
  const int tid = threadIdx.x;
  const int warp = __shfl_sync(0xffffffffu, tid >> 5, 0), lane = tid & 31;
  const int b = blockIdx.x;
  const int cl = b >> 1;
  const int jf = cl & 7;
  const int it_ = ((cl >> 3) << 1) | (b & 1);
  const int d0 = b * 4;

  const int kch = warp / 3;
  const int kpart = (warp - 3 * kch + (kch < 2 ? kch : 2)) % 3;
  const int kk0 = kpart == 0 ? 0 : (kpart == 1 ? 6 : 11), nks = kpart == 0 ? 6 : 5;
  uint32_t pw0[2], pw1[2], pldt;
  {
    unsigned short raw[9];
    int n0 = 8 * kk0 + lane, n1 = n0 + 32;
    n0 = (d0 + kch) * NS_ + n0;
    n1 = (d0 + kch) * NS_ + (n1 < NS_ ? n1 : NS_ - 1);
    asm volatile("ld.global.nc.u16 %0, [%9];\n\tld.global.nc.u16 %1, [%10];\n\tld.global.nc.u16 %2, [%11];\n\t"
                 "ld.global.nc.u16 %3, [%12];\n\tld.global.nc.u16 %4, [%13];\n\tld.global.nc.u16 %5, [%14];\n\t"
                 "ld.global.nc.u16 %6, [%15];\n\tld.global.nc.u16 %7, [%16];\n\tld.global.nc.u16 %8, [%17];"
                 : "=h"(raw[0]), "=h"(raw[1]), "=h"(raw[2]), "=h"(raw[3]), "=h"(raw[4]), "=h"(raw[5]), "=h"(raw[6]), "=h"(raw[7]), "=h"(raw[8])
                 : "l"(P.log_A_real + n0), "l"(P.A_imag + n0), "l"(P.C_real + n0), "l"(P.C_imag + n0),
                   "l"(P.log_A_real + n1), "l"(P.A_imag + n1), "l"(P.C_real + n1), "l"(P.C_imag + n1), "l"(P.log_dt + d0 + kch));
  if (lane == 0) {
    if (warp == 8) {
      mbar_init(bars + 8 * (B_FULL + 0), 1); mbar_init(bars + 8 * (B_FULL + 2), 1); mbar_init(bars + 8 * (B_FULL + 4), 1);
      mbar_init(bars + 8 * (B_XFULL + 0), 1); mbar_init(bars + 8 * (B_XFULL + 2), 1); mbar_init(bars + 8 * (B_XFULL + 4), 1);
    } else if (warp == 9) {
      mbar_init(bars + 8 * (B_FULL + 1), 1); mbar_init(bars + 8 * (B_FULL + 3), 1);
      mbar_init(bars + 8 * (B_XFULL + 1), 1); mbar_init(bars + 8 * (B_XFULL + 3), 1); mbar_init(bars + 8 * (B_XFULL + 5), 1);
    } else {
      const int wi = warp < 8 ? warp : warp - 2;
#pragma unroll
      for (int r = 0; r < 5; r++) {
        int i = wi + 10 * r + 5;
        if (i >= B_XFULL) i += 6;
        uint32_t cnt = 1;
        if ((i >= B_EMPTY && i < B_EMPTY + 5) || (i >= B_XFREE && i < B_XFREE + 8) || (i >= B_SENT && i < B_SENT + 8) || i == B_ADONE || i == B_ADONE + 1) cnt = 8;
        if (i == B_RRDY || i == B_KSUM) cnt = 2;
        if (i == B_GOT) cnt = 7;
        mbar_init(bars + 8 * i, cnt);
      }
    }
    asm volatile("fence.mbarrier_init.release.cluster;" ::: "memory");
  }
  __syncwarp();
    pw0[0] = (uint32_t)raw[0] | ((uint32_t)raw[1] << 16); pw1[0] = (uint32_t)raw[2] | ((uint32_t)raw[3] << 16);
    pw0[1] = (uint32_t)raw[4] | ((uint32_t)raw[5] << 16); pw1[1] = (uint32_t)raw[6] | ((uint32_t)raw[7] << 16);
    pldt = raw[8];
  }
  TM_IF(tid == 0, 21);

  auto issue_stage = [&](int s, int slot) {
    const uint32_t dst = sb + SM_RING + slot * 16384;
    const uint32_t fb = bars + 8 * (B_FULL + slot);
    if (s < 32) {
      const int f0 = jf * 224 + ((s >> 4) << 7);
      const int k0 = (s & 15) * 32;
      mbar_expect(fb, 16384);
      if (jf == 7 && s >= 16) {
        tma2d(dst, &M.Wg, f0, k0, fb);
        tma2d(dst + 4096, &M.Wg, f0 + 64, k0, fb);
        tma2d(dst + 8192, &M.Wu, f0, k0, fb);
        tma2d(dst + 12288, &M.Wu, f0 + 64, k0, fb);
      } else {
        tma3d(dst, &M.Wg3[jf & 1], 0, k0, f0 >> 6, fb);
        tma3d(dst + 8192, &M.Wu3[jf & 1], 0, k0, f0 >> 6, fb);
      }
    } else {
      const int s2 = s - 32;
      const int p = (jf + 1 + (s2 >> 1)) & 7;
      mbar_expect(fb, 14336);
      tma2d(dst, &M.Wd, p * 64, jf * 224 + (s2 & 1) * 112, fb);
    }
  };
  auto issue_x = [&](int kb) {
    mbar_expect(bars + 8 * (B_XFULL + kb), 16384);
    tma2d(sb + SM_X + kb * 16384, &M.X, kb * 64, it_ * 128, bars + 8 * (B_XFULL + kb));
  };
  {
    const int g = lane >> 2, q = lane & 3;
    const float dtf = bf16r(expf(bf_lo(pldt)));
    const int pro = kch * 128 + 8 * kk0;
    float4* prm = (float4*)(smem + SM_PR) + pro;
    float2* prq = (float2*)(smem + SM_PR + 512 * 16) + pro;
    const bool valid1 = lane + 32 < 8 * nks;
    float m0 = fmaxf(fmaxf(fabsf(bf_lo(pw1[0])), fabsf(bf_hi(pw1[0]))), fmaxf(fabsf(bf_lo(pw1[1])), fabsf(bf_hi(pw1[1])))) * dtf;
#pragma unroll
    for (int o = 16; o > 0; o >>= 1) m0 = fmaxf(m0, __shfl_xor_sync(0xffffffffu, m0, o));
    TM_IF(tid == 0 && m0 >= 0.f, 0);
    if (m0 >= 0.f || m0 != m0) {
      if (tid == 256) {
        issue_x(0); issue_stage(0, 0); issue_stage(2, 2); issue_x(2); issue_stage(4, 4); issue_x(4);
      } else if (tid == 288) {
        issue_stage(1, 1); issue_x(1); issue_stage(3, 3); issue_x(3); issue_x(5);
      }
    }
    __syncwarp();
    const uint32_t e0 = min(max(__float_as_uint(m0) >> 23, 1u), 253u);
    const float sc = __uint_as_float((254u - e0) << 23);
    const float us = 2.f * __uint_as_float(e0 << 23);
    float pe = 0.f;
#pragma unroll
    for (int r = 0; r < 2; r++) {
      float4 v;
      v.x = -bf16r(expf(bf_lo(pw0[r]))) * dtf;
      v.y = bf_hi(pw0[r]) * dtf;
      v.z = bf_lo(pw1[r]) * dtf * sc;
      v.w = bf_hi(pw1[r]) * dtf * sc;
      const cpx Q = cexp_fast(v.x * 64.f, v.y * 64.f);
      const cpx We = cexp_fast(v.x * 2048.f, v.y * 2048.f);
      if (r == 0 || valid1) {
        pe += v.z * We.r - v.w * We.i;
        prm[lane + 32 * r] = v;
        prq[lane + 32 * r] = make_float2(Q.r, Q.i);
      }
    }
#pragma unroll
    for (int o = 16; o > 0; o >>= 1) pe += __shfl_xor_sync(0xffffffffu, pe, o);
    __syncwarp();
    TM_IF(tid == 0, 1);
    float T[5][4];
#pragma unroll
    for (int i = 0; i < 20; i++) T[i >> 2][i & 3] = 0.f;
    const float gf = (float)g;
#pragma unroll 1
    for (int ks = 0; ks < nks; ks++) {
      KOps o1, o2;
      kgen_ops(o1, prm[8 * ks + q], prq[8 * ks + q], gf);
      kgen_ops(o2, prm[8 * ks + 4 + q], prq[8 * ks + 4 + q], gf);
      kgen_mma(T, o1, o2);
    }
    float* kp = (float*)(smem + SM_X + 6 * 16384) + warp * KC_STRIDE + 8 * g + 2 * q;
#pragma unroll
    for (int k = 0; k < 5; k++) {
      *(float2*)(kp + 128 * k) = make_float2(T[k][0] * us, T[k][1] * us);
      *(float2*)(kp + 128 * k + 64) = make_float2(T[k][2] * us, T[k][3] * us);
    }
    if (lane == 0) { kp[640] = pe * us; kp[641] = 0.f; }
    TM_IF(tid == 0, 2);
  }
  __syncthreads();

  if (warp >= 8) {
    asm volatile("setmaxnreg.dec.sync.aligned.u32 104;");
    if (warp < 10) {
      if (lane == 0) {
        int slot = (warp == 8) ? 1 : 0;
        uint32_t ph = 0;
#pragma unroll 1
        for (int s = (warp == 8) ? 6 : 5; s < 48; s += 2) {
          if (s == 10) { mbar_wait(bars + 8 * B_KSUM, 0); issue_x(6); issue_x(7); }
          mbar_wait(bars + 8 * (B_EMPTY + slot), ph);
          issue_stage(s, slot);
          slot += 2;
          if (slot >= 5) { slot -= 5; ph ^= 1; }
        }
      }
      __syncwarp();
      {
        const uint4 gw0 = *(const uint4*)(P.gate_w + lane * 16);
        const uint4 gw1 = *(const uint4*)(P.gate_w + lane * 16 + 8);
        uint4 xa[8], xb[8];
#pragma unroll
        for (int i = 0; i < 8; i++) {
          xa[i] = *(const uint4*)(P.x + (b * 16 + (warp - 8) * 8 + i) * D_ + lane * 16);
          xb[i] = *(const uint4*)(P.x + (b * 16 + (warp - 8) * 8 + i) * D_ + lane * 16 + 8);
        }
        float sg[8];
#pragma unroll
        for (int i = 0; i < 8; i++) {
          const uint32_t pr[8] = {hmul2_bf16(xa[i].x, gw0.x), hmul2_bf16(xa[i].y, gw0.y), hmul2_bf16(xa[i].z, gw0.z), hmul2_bf16(xa[i].w, gw0.w),
                                  hmul2_bf16(xb[i].x, gw1.x), hmul2_bf16(xb[i].y, gw1.y), hmul2_bf16(xb[i].z, gw1.z), hmul2_bf16(xb[i].w, gw1.w)};
          float s = 0.f;
#pragma unroll
          for (int k = 0; k < 8; k++) s += bf_lo(pr[k]) + bf_hi(pr[k]);
          sg[i] = s;
        }
#pragma unroll
        for (int o = 16; o > 0; o >>= 1) {
#pragma unroll
          for (int i = 0; i < 8; i++) sg[i] += __shfl_xor_sync(0xffffffffu, sg[i], o);
        }
        float z = sg[0];
#pragma unroll
        for (int i = 1; i < 8; i++) z = (lane == i) ? sg[i] : z;
        if (lane < 8) g_gate[b * 16 + (warp - 8) * 8 + lane] = bf16r(1.f / (1.f + expf(-bf16r(z))));
      }
      bar_sync(3, 64);
      if (tid == 288) asm volatile("red.release.gpu.global.add.u32 [%0], 1;" ::"l"(&g_done1) : "memory");
      TM_IF(tid == 256, 16);
      if (warp == 8) {
        if (lane >= 1 && lane < 8) {
          const uint32_t tag = ld_epoch() + 1;
          const uint32_t* fp = g_flag + ((it_ * 8 + jf) * 8 + ((jf - lane) & 7));
          int itc = 0;
          while (ld_acquire(fp) != tag) { __nanosleep(100); if (++itc > SPIN_LIMIT) FAIL(-2, lane); }
          mbar_arrive(bars + 8 * B_GOT);
          TM_IF(lane == 7, 25);
        }
      } else if (lane == 0) {
        const uint32_t tag = ld_epoch() + 1;
#pragma unroll 1
        for (int rnd = 0; rnd < 2; rnd++) {
          if (rnd == 1) {
            int itc = 0;
            while ((int)(ld_acquire(&g_done1) - (uint32_t)NCTA * tag) < 0) { if (++itc > SPIN_LIMIT) FAIL(-1, 0); }
            mbar_wait(bars + 8 * (B_ADONE + 1), 0);
          } else {
            mbar_wait_lazy<100>(bars + 8 * B_ADONE, 0);
          }
          TM_IF(true, 24);
#pragma unroll
          for (int v = 0; v < 2; v++)
            asm volatile("cp.async.bulk.global.shared::cta.bulk_group [%0], [%1], %2;"
                         ::"l"(g_aT + (d0 + 2 * v + rnd) * L_), "r"(sb + SM_X + CV_R + (2 * v + rnd) * R_CH), "r"(4096) : "memory");
          asm volatile("cp.async.bulk.commit_group;" ::: "memory");
          asm volatile("cp.async.bulk.wait_group 0;" ::: "memory");
          asm volatile("fence.proxy.async.global;" ::: "memory");
          asm volatile("red.release.gpu.global.add.u32 [%0], 1;" ::"l"(g_cnt + 32 * (b >> 4)) : "memory");
        }
        TM_IF(true, 26);
        {
          int itc = 0;
          while ((int)(ld_acquire(g_cnt + 32 * jf) - 32u * tag) < 0) { if (++itc > SPIN_LIMIT) FAIL(-3, 0); }
        }
        TM_IF(true, 23);
        asm volatile("fence.proxy.async.global;" ::: "memory");
        mbar_expect(bars + 8 * B_ATILE, 16384);
        tma2d(sb + SM_AT, &M.AT, it_ * 128, jf * 64, bars + 8 * B_ATILE);
        tma2d(sb + SM_AT + 8192, &M.AT, it_ * 128 + 64, jf * 64, bars + 8 * B_ATILE);
      }
      __syncwarp();
    } else {
      const int w = warp - 10;
      const int wt = tid - 320;
      {
        const float2* kp = (const float2*)(smem + SM_X + 6 * 16384);
        uint32_t* kb = (uint32_t*)(smem + SM_KB);
#pragma unroll
        for (int ch = 0; ch < 4; ch++) {
#pragma unroll
          for (int i = 0; i < 6; i++) {
            const int o = wt + 64 * i;
            if (i < 5 || o < 321) {
              const float2 a0 = kp[(3 * ch) * (KC_STRIDE / 2) + o], a1 = kp[(3 * ch + 1) * (KC_STRIDE / 2) + o], a2 = kp[(3 * ch + 2) * (KC_STRIDE / 2) + o];
              kb[ch * (KC_STRIDE / 2) + o] = pack_bf16(a0.x + a1.x + a2.x, a0.y + a1.y + a2.y);
            }
          }
        }
      }
      fence_async();
      bar_sync(1, 64);
      if (lane == 0) mbar_arrive(bars + 8 * B_KSUM);
      {
        const uint32_t zz = *(volatile uint32_t*)&g_zero;
        uint2 ur[4][8];
#pragma unroll
        for (int i = 0; i < 4; i++) {
#pragma unroll
          for (int r = 0; r < 8; r++) {
            uint32_t ck;
            asm volatile("nanosleep.u32 90;\n\tmov.u32 %0, %%clock;" : "=r"(ck) :: "memory");
            asm volatile("ld.global.nc.v2.u32 {%0,%1}, [%2];" : "=r"(ur[i][r].x), "=r"(ur[i][r].y)
                         : "l"(P.x + ((wt + 64 * i) * 8 + r) * D_ + d0 + (ck & zz)));
          }
        }
        mbar_wait_lazy<200>(bars + 8 * (B_XFREE + 3), 0);
        TM_IF(wt == 0, 18);
#pragma unroll
        for (int i = 0; i < 4; i++) {
          const int item = wt + 64 * i;
          const int c = item >> 1, hh = item & 1;
#pragma unroll
          for (int ch = 0; ch < 4; ch++) {
            uint32_t v[4];
#pragma unroll
            for (int k = 0; k < 4; k++) {
              const uint32_t lo = (ch < 2) ? ur[i][7 - 2 * k].x : ur[i][7 - 2 * k].y;
              const uint32_t hi = (ch < 2) ? ur[i][6 - 2 * k].x : ur[i][6 - 2 * k].y;
              v[k] = (ch & 1) ? __byte_perm(lo, hi, 0x7632) : __byte_perm(lo, hi, 0x5410);
            }
            *(uint4*)(smem + SM_X + CV_R + ch * R_CH + (1 - hh) * R_HALF + (127 - c) * 16) = make_uint4(v[0], v[1], v[2], v[3]);
          }
        }
        if (lane < 28) {
#pragma unroll
          for (int z = 0; z < 4; z++)
            *(uint4*)(smem + SM_X + CV_R + (4 * w + z) * R_HALF + (128 + lane) * 16) = make_uint4(0, 0, 0, 0);
        }
      }
      auto part_store = [&](int s) {
        mbar_wait_lazy<100>(bars + 8 * (B_SENT + s), 0);
        const int fi = (it_ * 8 + ((jf + 1 + s) & 7)) * 8 + jf;
#pragma unroll
        for (int v = 0; v < 2; v++)
          asm volatile("cp.async.bulk.global.shared::cta.bulk_group [%0], [%1], %2;"
                       ::"l"(g_part + (size_t)fi * 1024 + v * 512), "r"(sb + SM_X + part_slot(s, v)), "r"(8192) : "memory");
        asm volatile("cp.async.bulk.commit_group;" ::: "memory");
      };
      {
#pragma unroll 1
      for (int G = w; G < 8; G += 2) {
        const int n = 32 * G + lane;
        uint4 c0[4], c1[4];
        if (G >= 4) {
#pragma unroll
          for (int ch = 0; ch < 4; ch++) {
            const uint8_t* kc = smem + SM_KB + ch * KC_STRIDE * 2;
            const uint32_t a = *(const unsigned short*)(kc + (384 + n) * 2), bb = *(const unsigned short*)(kc + (385 + n) * 2);
            const uint32_t aa = a | (a << 16), b2 = bb | (bb << 16);
            const uint32_t tie = (n & 1) ? bb : a;
            c0[ch] = make_uint4(aa, a | (tie << 16), b2, b2);
            c1[ch] = make_uint4(aa, tie | (bb << 16), b2, b2);
          }
        } else if (G >= 2) {
#pragma unroll
          for (int ch = 0; ch < 4; ch++) {
            const uint8_t* kc = smem + SM_KB + ch * KC_STRIDE * 2;
            const uint32_t w0 = *(const uint32_t*)(kc + (256 + 2 * n) * 2), w1 = *(const uint32_t*)(kc + (258 + 2 * n) * 2);
            c0[ch] = make_uint4(dup_lo(w0), dup_hi(w0), __byte_perm(w0, w1, 0x5432), dup_lo(w1));
            c1[ch] = make_uint4(w0, dup_hi(w0), dup_lo(w1), dup_lo(w1));
          }
        } else if (G == 1) {
#pragma unroll
          for (int ch = 0; ch < 4; ch++) {
            const uint8_t* kc = smem + SM_KB + ch * KC_STRIDE * 2;
            const uint2 w01 = *(const uint2*)(kc + (128 + 4 * n) * 2);
            const uint32_t w2 = *(const uint32_t*)(kc + (132 + 4 * n) * 2);
            c0[ch] = make_uint4(w01.x, dup_lo(w01.y), w01.y, dup_lo(w2));
            c1[ch] = make_uint4(__byte_perm(w01.x, w01.y, 0x5432), dup_lo(w01.y), __byte_perm(w01.y, w2, 0x5432), dup_lo(w2));
          }
        } else {
#pragma unroll
          for (int ch = 0; ch < 4; ch++) {
            const uint8_t* kc = smem + SM_KB + ch * KC_STRIDE * 2;
            const uint4 wv = *(const uint4*)(kc + (8 * n) * 2);
            const uint32_t w4 = *(const uint32_t*)(kc + (8 * n + 8) * 2);
            c0[ch] = make_uint4(__byte_perm(wv.x, wv.y, 0x5432), __byte_perm(wv.y, wv.z, 0x5432), __byte_perm(wv.z, wv.w, 0x5432), __byte_perm(wv.w, w4, 0x5432));
            c1[ch] = make_uint4(wv.y, wv.z, wv.w, (n == 31) ? dup_lo(w4) : w4);
          }
          if (lane < 8) {
            const int ch = lane >> 1, hi = lane & 1;
            const uint32_t k01 = *(const uint32_t*)(smem + SM_KB + ch * KC_STRIDE * 2);
            uint8_t* e = smem + SM_X + CV_E + ch * E_CH + hi * 16;
            *(uint4*)e = make_uint4(0, 0, 0, hi ? (k01 << 16) : 0u);
            *(uint4*)(e + E_COPY) = make_uint4(0, 0, 0, hi ? k01 : 0u);
          }
        }
#pragma unroll
        for (int ch = 0; ch < 4; ch++) {
          uint8_t* e = smem + SM_X + CV_E + ch * E_CH + (n + 2) * 16;
          *(uint4*)e = c0[ch];
          *(uint4*)(e + E_COPY) = c1[ch];
        }
      }
        fence_async();
        __syncwarp();
        if (lane == 0) mbar_arrive(bars + 8 * B_RRDY);
        TM_IF(wt == 0, 19);
      }
      if (lane == 0) {
        const uint32_t tag = ld_epoch() + 1;
        auto publish = [&](int s) {
          asm volatile("fence.proxy.async.global;" ::: "memory");
          st_release(g_flag + ((it_ * 8 + ((jf + 1 + s) & 7)) * 8 + jf), tag);
          TM_IF(true, 3 + s);
        };
#pragma unroll 1
        for (int s = w; s < 7; s += 2) {
          {
            part_store(s);
            asm volatile("cp.async.bulk.wait_group.read 0;" ::: "memory");
            mbar_arrive(bars + 8 * (B_STF + s));
          }
          if (s >= 2 && s < 6) {
            asm volatile("cp.async.bulk.wait_group 1;" ::: "memory");
            publish(s - 2);
          }
          if (s >= 4) {
            asm volatile("cp.async.bulk.wait_group 0;" ::: "memory");
            publish(s);
          }
        }
      }
      __syncwarp();
    }
    bar_sync(2, 128);
    if (tid == 256) {
      const uint32_t tk = atomicAdd(&g_exit, 1u);
      if (tk == NCTA - 1) {
        g_exit = 0;
        *(volatile uint32_t*)&g_epoch = ld_epoch() + 1;
      }
    }
    TM_IF(tid == 256, 13);
  } else {
    asm volatile("setmaxnreg.inc.sync.aligned.u32 200;");
    const int wg = warp >> 2;
    const int g = lane >> 2, q = lane & 3;
    const uint32_t dsk = *(const uint32_t*)(P.D_skip + d0 + 2 * wg);
    uint32_t hf[56];
    {
      float acc[128];
#pragma unroll
      for (int i = 0; i < 128; i++) zero_reg(acc[i]);
#pragma unroll 1
      for (int st = 0; st < 16; st++) {
        const int slot = st % 5;
        if ((st & 1) == 0) mbar_wait(bars + 8 * (B_XFULL + (st >> 1)), 0);
        mbar_wait(bars + 8 * (B_FULL + slot), (st / 5) & 1);
        const uint64_t da = mkdesc(sb + SM_X + (st >> 1) * 16384 + wg * 8192 + (st & 1) * 64, 16, 1024, 1);
        const uint64_t db = mkdesc(sb + SM_RING + slot * 16384, 4096, 1024, 1);
        wg_fence();
        wgmma_ss_n256(acc, da, db);
        wgmma_ss_n256(acc, da + 2, db + 128);
        wg_commit();
        if (st > 0) {
          wg_wait<1>();
          if (lane == 0) mbar_arrive(bars + 8 * (B_EMPTY + (st - 1) % 5));
        }
      }
      wg_wait<0>();
      if (lane == 0) mbar_arrive(bars + 8 * (B_EMPTY + 15 % 5));
#pragma unroll
      for (int m = 0; m < 16; m++) {
        hf[2 * m] = hmul2_bf16(pack_bf16(acc[4 * m], acc[4 * m + 1]), pack_bf16(acc[64 + 4 * m], acc[64 + 4 * m + 1]));
        hf[2 * m + 1] = hmul2_bf16(pack_bf16(acc[4 * m + 2], acc[4 * m + 3]), pack_bf16(acc[64 + 4 * m + 2], acc[64 + 4 * m + 3]));
      }
    }
    float accA[32], accB[32];
    auto issue_half = [&](float (&acc)[32], int s, auto half_tag) {
      constexpr int half = decltype(half_tag)::value;
      if (half == 0) {
#pragma unroll
        for (int i = 0; i < 32; i++) zero_reg(acc[i]);
      }
      const int st = 32 + 2 * s + half;
      const int slot = st % 5;
      mbar_wait(bars + 8 * (B_FULL + slot), (st / 5) & 1);
      uint32_t sbase;
      asm volatile("mov.b32 %0, %1;" : "=r"(sbase) : "r"(sb + SM_RING + slot * 16384));
      const uint64_t db = mkdesc(sbase, 1024, 1024, 1);
      wg_fence();
#pragma unroll
      for (int k = 0; k < 7; k++) {
        const int ks = 7 * half + k;
        wgmma_rs_n64t(acc, hf[4 * ks], hf[4 * ks + 1], hf[4 * ks + 2], hf[4 * ks + 3], db + k * 128);
      }
      wg_commit();
    };
    auto release = [&](int st) { if (lane == 0) mbar_arrive(bars + 8 * (B_EMPTY + st % 5)); };
    using H0 = IC<0>;
    using H1 = IC<1>;
    {
      float accg[48], accu[48];
#pragma unroll
      for (int i = 0; i < 48; i++) { zero_reg(accg[i]); zero_reg(accu[i]); }
      const uint32_t xrow = sb + SM_X + (wg * 64 + (warp & 3) * 16 + (lane & 15)) * 128;
      const uint32_t xsw = lane & 7, xhi = lane >> 4;
      uint32_t a0[4], a1[4], a2[4], a3[4];
#pragma unroll 1
      for (int kb = 0; kb < 8; kb++) {
        const uint32_t xb = xrow + kb * 16384;
        {
          const int st = 16 + 2 * kb, slot = st % 5;
          ldsm4(a0, xb + (((0 + xhi) ^ xsw) << 4));
          ldsm4(a1, xb + (((2 + xhi) ^ xsw) << 4));
          mbar_wait(bars + 8 * (B_FULL + slot), (st / 5) & 1);
          const uint64_t db = mkdesc(sb + SM_RING + slot * 16384, 4096, 1024, 1);
          wg_fence();
          wgmma_rs_n96(accg, a0[0], a0[1], a0[2], a0[3], db);
          wgmma_rs_n96(accu, a0[0], a0[1], a0[2], a0[3], db + 512);
          wgmma_rs_n96(accg, a1[0], a1[1], a1[2], a1[3], db + 128);
          wgmma_rs_n96(accu, a1[0], a1[1], a1[2], a1[3], db + 128 + 512);
          wg_commit();
          wg_wait<1>();
          if (kb > 0 && lane == 0) mbar_arrive(bars + 8 * (B_EMPTY + (st - 1) % 5));
        }
        {
          const int st = 17 + 2 * kb, slot = st % 5;
          ldsm4(a2, xb + (((4 + xhi) ^ xsw) << 4));
          ldsm4(a3, xb + (((6 + xhi) ^ xsw) << 4));
          mbar_wait(bars + 8 * (B_FULL + slot), (st / 5) & 1);
          const uint64_t db = mkdesc(sb + SM_RING + slot * 16384, 4096, 1024, 1);
          wg_fence();
          wgmma_rs_n96(accg, a2[0], a2[1], a2[2], a2[3], db);
          wgmma_rs_n96(accu, a2[0], a2[1], a2[2], a2[3], db + 512);
          wgmma_rs_n96(accg, a3[0], a3[1], a3[2], a3[3], db + 128);
          wgmma_rs_n96(accu, a3[0], a3[1], a3[2], a3[3], db + 128 + 512);
          wg_commit();
          wg_wait<1>();
          if (lane == 0) {
            mbar_arrive(bars + 8 * (B_EMPTY + (st - 1) % 5));
            if (kb == 3) mbar_arrive(bars + 8 * (B_XFREE + 3));
          }
        }
      }
      issue_half(accA, 0, H0{});
      wg_wait<1>();
      if (lane == 0) { mbar_arrive(bars + 8 * (B_EMPTY + 31 % 5)); mbar_arrive(bars + 8 * (B_XFREE + 7)); }
#pragma unroll
      for (int m = 0; m < 12; m++) {
        hf[32 + 2 * m] = hmul2_bf16(pack_bf16(accg[4 * m], accg[4 * m + 1]), pack_bf16(accu[4 * m], accu[4 * m + 1]));
        hf[32 + 2 * m + 1] = hmul2_bf16(pack_bf16(accg[4 * m + 2], accg[4 * m + 3]), pack_bf16(accu[4 * m + 2], accu[4 * m + 3]));
      }
    }
    auto send_pass = [&](float (&acc)[32], int s) {
      uint4* dst = (uint4*)(smem + SM_X + part_slot(s, wg) + (warp & 3) * 2048) + lane;
#pragma unroll
      for (int c = 0; c < 4; c++) {
        uint4 v;
        v.x = pack_bf16(acc[8 * c], acc[8 * c + 1]); v.y = pack_bf16(acc[8 * c + 2], acc[8 * c + 3]);
        v.z = pack_bf16(acc[8 * c + 4], acc[8 * c + 5]); v.w = pack_bf16(acc[8 * c + 6], acc[8 * c + 7]);
        dst[c * 32] = v;
      }
    };
    auto send_signal = [&](int s) {
      fence_async();
      __syncwarp();
      if (lane == 0) mbar_arrive(bars + 8 * (B_SENT + s));
    };
    auto part_load = [&](uint4 (&v)[4], int k) {
      const uint4* sp = g_part + (size_t)(((it_ * 8 + jf) * 8 + ((jf - k) & 7)) * 8 + warp) * 128 + lane;
#pragma unroll
      for (int c = 0; c < 4; c++) v[c] = ld_cg4(sp + c * 32);
    };
    auto part_add = [&](const uint4 (&v)[4]) {
#pragma unroll
      for (int c = 0; c < 4; c++) {
        accA[8 * c] += bf_lo(v[c].x); accA[8 * c + 1] += bf_hi(v[c].x); accA[8 * c + 2] += bf_lo(v[c].y); accA[8 * c + 3] += bf_hi(v[c].y);
        accA[8 * c + 4] += bf_lo(v[c].z); accA[8 * c + 5] += bf_hi(v[c].z); accA[8 * c + 6] += bf_lo(v[c].w); accA[8 * c + 7] += bf_hi(v[c].w);
      }
    };
    issue_half(accA, 0, H1{}); wg_wait<1>(); release(32);
    mbar_wait(bars + 8 * (B_XFREE + 7), 0);
    issue_half(accB, 1, H0{}); wg_wait<1>(); release(33); send_pass(accA, 0);
    issue_half(accB, 1, H1{}); send_signal(0); wg_wait<1>(); release(34);
    issue_half(accA, 2, H0{}); wg_wait<1>(); release(35); send_pass(accB, 1);
    issue_half(accA, 2, H1{}); send_signal(1); wg_wait<1>(); release(36);
    issue_half(accB, 3, H0{}); wg_wait<1>(); release(37); send_pass(accA, 2);
    issue_half(accB, 3, H1{}); send_signal(2); wg_wait<1>(); release(38);
    issue_half(accA, 4, H0{}); wg_wait<1>(); release(39); send_pass(accB, 3);
    issue_half(accA, 4, H1{}); send_signal(3); wg_wait<1>(); release(40);
    issue_half(accB, 5, H0{}); wg_wait<1>(); release(41); mbar_wait(bars + 8 * (B_STF + 0), 0); send_pass(accA, 4);
    issue_half(accB, 5, H1{}); send_signal(4); wg_wait<1>(); release(42);
    wg_wait<0>(); send_pass(accB, 5);
    {
      TM_IF(tid == 0, 10);
      const int w = warp & 3;
      mbar_wait(bars + 8 * B_RRDY, 0);
      TM_IF(tid == 0, 11);
      const uint32_t zero = lds32(sb + SM_X + CV_R + (2 * wg + 1) * R_CH + 128 * 16);
      const int c = tid & 127;
      const float* Sr = (const float*)(smem + SM_X + CV_S + wg * S_WG) + (127 - c);
      float* Sw = (float*)(smem + SM_X + CV_S + wg * S_WG) + w * 16 * S_PITCH + g * S_PITCH + 2 * q;
      uint32_t fa[4][4], fb[4][4];
      uint32_t ares[8] = {0, 0, 0, 0, 0, 0, 0, 0}, rv[8];
      auto load_u = [&](int ch) {
        const uint4 r0v = *(const uint4*)(smem + SM_X + CV_R + ch * R_CH + (127 - c) * 16);
        const uint4 r1v = *(const uint4*)(smem + SM_X + CV_R + ch * R_CH + R_HALF + (127 - c) * 16);
        rv[0] = r0v.x; rv[1] = r0v.y; rv[2] = r0v.z; rv[3] = r0v.w; rv[4] = r1v.x; rv[5] = r1v.y; rv[6] = r1v.z; rv[7] = r1v.w;
      };
#define POST(r2, dk2)                                                                              \
      {                                                                                            \
        float y_[2];                                                                               \
        _Pragma("unroll") for (int t2 = 0; t2 < 2; t2++) {                                         \
          const int r0 = 2 * (r2) + t2;                                                            \
          const float s1 = c >= 1 ? Sr[(16 + r0) * S_PITCH + 1] : 0.f;                             \
          const float s2 = c >= 2 ? Sr[(32 + r0) * S_PITCH + 2] : 0.f;                             \
          const float s3 = c >= 3 ? Sr[(48 + r0) * S_PITCH + 3] : 0.f;                             \
          y_[t2] = (Sr[r0 * S_PITCH] + s1) + (s2 + s3);                                            \
        }                                                                                          \
        ares[r2] = hadd2_bf16(pack_bf16(y_[0], y_[1]), hmul2_bf16(__byte_perm(rv[7 - (r2)], rv[7 - (r2)], 0x1032), dk2)); \
      }
      auto store_a = [&](int ch) {
        uint4* ap = (uint4*)(smem + SM_X + CV_R + ch * R_CH + c * 32);
        ap[0] = make_uint4(ares[0], ares[1], ares[2], ares[3]);
        ap[1] = make_uint4(ares[4], ares[5], ares[6], ares[7]);
        fence_async();
      };
      const uint32_t eoff = ((g & 1) ? E_COPY : 0) + (16 * w + (g & ~1) + 2 * q) * 2;
      const uint32_t dkA = dup_lo(dsk), dkB = dup_hi(dsk);
      {
        const int ch = 2 * wg;
        const uint32_t ebase = sb + SM_X + CV_E + ch * E_CH + eoff;
        const uint64_t de = mkdesc(sb + SM_X + CV_R + ch * R_CH, R_HALF, 128, 0);
        conv_load4<0>(fa, ebase, zero);
        conv_load4<4>(fb, ebase, zero);
        CONV_CHANNEL(mbar_wait(bars + 8 * (B_STF + 1), 0); mbar_wait(bars + 8 * (B_STF + 2), 0); mbar_wait(bars + 8 * (B_STF + 3), 0); mbar_wait(bars + 8 * (B_STF + 4), 0);, send_signal(5);, )
        TM_IF(tid == 0, 14);
      }
      issue_half(accA, 6, H0{});
      issue_half(accA, 6, H1{});
      bar_sync(6 + wg, 128);
      POST(0, dkA) POST(1, dkA) POST(2, dkA) POST(3, dkA) POST(4, dkA) POST(5, dkA) POST(6, dkA) POST(7, dkA)
      store_a(2 * wg);
      __syncwarp();
      if (lane == 0) mbar_arrive(bars + 8 * B_ADONE);
      {
        const int ch = 2 * wg + 1;
        const uint32_t ebase = sb + SM_X + CV_E + ch * E_CH + eoff;
        const uint64_t de = mkdesc(sb + SM_X + CV_R + ch * R_CH, R_HALF, 128, 0);
        conv_load4<0>(fa, ebase, zero);
        conv_load4<4>(fb, ebase, zero);
        wg_wait<0>();
        send_pass(accA, 6);
        CONV_CHANNEL(bar_sync(6 + wg, 128);, send_signal(6);, )
        bar_sync(6 + wg, 128);
        TM_IF(tid == 0, 17);
        POST(0, dkB) POST(1, dkB) POST(2, dkB) POST(3, dkB) POST(4, dkB) POST(5, dkB) POST(6, dkB) POST(7, dkB)
        store_a(ch);
        __syncwarp();
        if (lane == 0) mbar_arrive(bars + 8 * (B_ADONE + 1));
      }
#undef POST
    }
    {
      uint4 v0[4], v1[4], v2[4], v3[4];
      mbar_wait(bars + 8 * B_GOT, 0);
      part_load(v0, 1);
      part_load(v1, 2);
      part_load(v2, 3);
      part_load(v3, 4);
      issue_half(accB, 7, H0{});
      issue_half(accB, 7, H1{});
#pragma unroll
      for (int i = 0; i < 32; i++) accA[i] = 0.f;
      part_add(v0); part_load(v0, 5);
      part_add(v1); part_load(v1, 6);
      part_add(v2); part_load(v2, 7);
      part_add(v3);
      part_add(v0);
      part_add(v1);
      part_add(v2);
    }
    TM_IF(tid == 0, 28);
    mbar_wait(bars + 8 * B_ATILE, 0);
    TM_IF(tid == 0, 29);
    const int row0 = it_ * 128 + warp * 16 + g;
    const float g0 = __uint_as_float(ld_cg1(g_gate + row0)), g1 = __uint_as_float(ld_cg1(g_gate + row0 + 8));
    uint32_t av[16];
    {
      const int dl = (lane & 7) + ((lane >> 4) << 3);
      const int chunk = 2 * (warp & 3) + ((lane >> 3) & 1);
      const uint32_t abase = sb + SM_AT + wg * 8192 + dl * 128 + ((chunk ^ (lane & 7)) << 4);
#pragma unroll
      for (int m2 = 0; m2 < 4; m2++) {
        asm volatile("ldmatrix.sync.aligned.m8n8.x4.trans.shared.b16 {%0,%1,%2,%3}, [%4];"
                     : "=r"(av[4 * m2]), "=r"(av[4 * m2 + 1]), "=r"(av[4 * m2 + 2]), "=r"(av[4 * m2 + 3]) : "r"(abase + m2 * 2048) : "memory");
      }
    }
    wg_wait<0>();
    const uint32_t gg0 = pack_bf16(g0, g0), gg1 = pack_bf16(g1, g1);
    const uint32_t og0 = pack_bf16(1.f - g0, 1.f - g0), og1 = pack_bf16(1.f - g1, 1.f - g1);
    uint32_t ov[16];
#pragma unroll
    for (int m = 0; m < 8; m++) {
      const uint32_t b0 = pack_bf16(accA[4 * m] + accB[4 * m], accA[4 * m + 1] + accB[4 * m + 1]);
      const uint32_t b1 = pack_bf16(accA[4 * m + 2] + accB[4 * m + 2], accA[4 * m + 3] + accB[4 * m + 3]);
      ov[2 * m] = hadd2_bf16(hmul2_bf16(gg0, av[2 * m]), hmul2_bf16(og0, b0));
      ov[2 * m + 1] = hadd2_bf16(hmul2_bf16(gg1, av[2 * m + 1]), hmul2_bf16(og1, b1));
    }
    {
      const uint32_t ob = sb + SM_X + CV_S + wg * S_WG + (warp & 3) * 2048;
      const int srow = (lane & 7) + ((lane >> 3) & 1) * 8;
#pragma unroll
      for (int m2 = 0; m2 < 4; m2++) {
        const int chunk = 2 * m2 + (lane >> 4);
        asm volatile("stmatrix.sync.aligned.m8n8.x4.shared.b16 [%0], {%1,%2,%3,%4};"
                     ::"r"(ob + srow * 128 + ((chunk ^ (srow & 7)) << 4)), "r"(ov[4 * m2]), "r"(ov[4 * m2 + 1]), "r"(ov[4 * m2 + 2]), "r"(ov[4 * m2 + 3]) : "memory");
      }
      __syncwarp();
#pragma unroll
      for (int i = 0; i < 4; i++) {
        const int r = 4 * i + (lane >> 3), chunk = lane & 7;
        const uint4 v = *(const uint4*)(smem + SM_X + CV_S + wg * S_WG + (warp & 3) * 2048 + r * 128 + ((chunk ^ (r & 7)) << 4));
        *(uint4*)(P.out + (it_ * 128 + warp * 16 + r) * D_ + jf * 64 + chunk * 8) = v;
      }
    }
    TM_IF(tid == 0, 30);
  }
}

typedef CUresult (*EncFn)(CUtensorMap*, CUtensorMapDataType, cuuint32_t, void*, const cuuint64_t*, const cuuint64_t*, const cuuint32_t*,
                          const cuuint32_t*, CUtensorMapInterleave, CUtensorMapSwizzle, CUtensorMapL2promotion, CUtensorMapFloatOOBfill);

struct HostState {
  bool ready;
  const void* key[4];
  Maps M;
};
HostState hs;

}

extern "C" void kernel_launch(void* const* d_in, const int* in_sizes, int n_in, void* d_out, int out_size) {
  (void)in_sizes; (void)n_in; (void)out_size;
  void* x = d_in[0];
  void* wg = d_in[8];
  void* wu = d_in[9];
  void* wd = d_in[10];
  if (!hs.ready || hs.key[0] != x || hs.key[1] != wg || hs.key[2] != wu || hs.key[3] != wd) {
    void* fn = nullptr;
    cudaDriverEntryPointQueryResult qr;
    cudaGetDriverEntryPoint("cuTensorMapEncodeTiled", &fn, cudaEnableDefault, &qr);
    EncFn enc = (EncFn)fn;
    const cuuint32_t es[3] = {1, 1, 1};
    const CUtensorMapDataType BF = CU_TENSOR_MAP_DATA_TYPE_BFLOAT16;
    const CUtensorMapInterleave IN = CU_TENSOR_MAP_INTERLEAVE_NONE;
    const CUtensorMapL2promotion PR = CU_TENSOR_MAP_L2_PROMOTION_L2_128B;
    const CUtensorMapFloatOOBfill OO = CU_TENSOR_MAP_FLOAT_OOB_FILL_NONE;
    {
      cuuint64_t gd[2] = {(cuuint64_t)D_, (cuuint64_t)L_}; cuuint64_t gs[1] = {(cuuint64_t)D_ * 2}; cuuint32_t box[2] = {64, 128};
      enc(&hs.M.X, BF, 2, x, gd, gs, box, es, IN, CU_TENSOR_MAP_SWIZZLE_128B, PR, OO);
    }
    {
      cuuint64_t gd[2] = {(cuuint64_t)F_, (cuuint64_t)D_}; cuuint64_t gs[1] = {(cuuint64_t)F_ * 2}; cuuint32_t box[2] = {64, 32};
      enc(&hs.M.Wg, BF, 2, wg, gd, gs, box, es, IN, CU_TENSOR_MAP_SWIZZLE_128B, PR, OO);
      enc(&hs.M.Wu, BF, 2, wu, gd, gs, box, es, IN, CU_TENSOR_MAP_SWIZZLE_128B, PR, OO);
      for (int o = 0; o < 2; o++) {
        cuuint64_t gd3[3] = {64, (cuuint64_t)D_, (cuuint64_t)(F_ / 64 - o)}; cuuint64_t gs3[2] = {(cuuint64_t)F_ * 2, 128};
        cuuint32_t box3[3] = {64, 32, 2};
        enc(&hs.M.Wg3[o], BF, 3, (char*)wg + 64 * o, gd3, gs3, box3, es, IN, CU_TENSOR_MAP_SWIZZLE_128B, PR, OO);
        enc(&hs.M.Wu3[o], BF, 3, (char*)wu + 64 * o, gd3, gs3, box3, es, IN, CU_TENSOR_MAP_SWIZZLE_128B, PR, OO);
      }
    }
    {
      cuuint64_t gd[2] = {(cuuint64_t)D_, (cuuint64_t)F_}; cuuint64_t gs[1] = {(cuuint64_t)D_ * 2}; cuuint32_t box[2] = {64, 112};
      enc(&hs.M.Wd, BF, 2, wd, gd, gs, box, es, IN, CU_TENSOR_MAP_SWIZZLE_128B, PR, OO);
    }
    {
      void* pa = nullptr;
      cudaGetSymbolAddress(&pa, g_aT);
      cuuint64_t gd[2] = {(cuuint64_t)L_, (cuuint64_t)D_}; cuuint64_t gs[1] = {(cuuint64_t)L_ * 2}; cuuint32_t box[2] = {64, 64};
      enc(&hs.M.AT, BF, 2, pa, gd, gs, box, es, IN, CU_TENSOR_MAP_SWIZZLE_128B, PR, OO);
    }
    cudaFuncSetAttribute(fused_kernel, cudaFuncAttributeMaxDynamicSharedMemorySize, SM_TOTAL);
    hs.key[0] = x; hs.key[1] = wg; hs.key[2] = wu; hs.key[3] = wd;
    hs.ready = true;
  }
  Params P;
  P.x = (const __nv_bfloat16*)d_in[0];
  P.log_A_real = (const __nv_bfloat16*)d_in[1];
  P.A_imag = (const __nv_bfloat16*)d_in[2];
  P.C_real = (const __nv_bfloat16*)d_in[3];
  P.C_imag = (const __nv_bfloat16*)d_in[4];
  P.log_dt = (const __nv_bfloat16*)d_in[5];
  P.D_skip = (const __nv_bfloat16*)d_in[6];
  P.gate_w = (const __nv_bfloat16*)d_in[11];
  P.w_gate = (const __nv_bfloat16*)wg;
  P.w_up = (const __nv_bfloat16*)wu;
  P.w_down = (const __nv_bfloat16*)wd;
  P.out = (__nv_bfloat16*)d_out;
  fused_kernel<<<NCTA, NTHREADS, SM_TOTAL>>>(hs.M, P);
}
```

```cpp
#include <cuda_runtime.h>
#include <cuda_bf16.h>
#include <cuda.h>
#include <stdint.h>

namespace {

constexpr int L_ = 2048, D_ = 512, F_ = 1792, NS_ = 128;
constexpr int NCTA = 128;
constexpr int NTHREADS = 384;

constexpr int SM_X = 0;
constexpr int SM_RING = 131072;
constexpr int KC_STRIDE = 656;
constexpr int SM_KB = 212992;
constexpr int SM_PR = SM_KB + 4 * KC_STRIDE * 2;
constexpr int SM_BAR = SM_PR + 512 * 24;
constexpr int SM_TOTAL = SM_BAR + 512;
constexpr int CV_R = 0;
constexpr int R_HALF = 156 * 16;
constexpr int R_CH = 2 * R_HALF;
constexpr int CV_E = 4 * R_CH;
constexpr int E_COPY = 4160;
constexpr int E_CH = 2 * E_COPY;
constexpr int CV_S = CV_E + 4 * E_CH;
constexpr int S_PITCH = 136;
constexpr int S_WG = 4 * 16 * S_PITCH * 4;
constexpr int SM_AT = SM_X;
static_assert(CV_S + 2 * S_WG + 8192 <= 131072, "conv region");
static_assert(SM_PR % 128 == 0, "alignment");

constexpr int B_FULL = 0, B_EMPTY = 5, B_XFULL = 10, B_XFREE = 18, B_ATILE = 26, B_RRDY = 27, B_ADONE = 28  , B_KSUM = 30, B_SENT = 35, B_GOT = 43, B_STF = 51;

__device__ uint4 g_part[16 * 8 * 8 * 8 * 4 * 32];
__device__ uint32_t g_flag[16 * 8 * 8];
__device__ __align__(1024) __nv_bfloat16 g_aT[D_ * L_];
__device__ float g_gate[L_];
__device__ uint32_t g_done1;
__device__ uint32_t g_cnt[8 * 32];
__device__ uint32_t g_exit;
__device__ uint32_t g_zero;
__device__ uint32_t g_epoch;

#define FAIL(a, ph) break
#define SPIN_LIMIT (1 << 22)
#define MBAR_LIMIT (1 << 20)
__device__ __forceinline__ uint32_t smem_u32(const void* p) { return (uint32_t)__cvta_generic_to_shared(p); }
__device__ __forceinline__ void mbar_init(uint32_t a, uint32_t c) { asm volatile("mbarrier.init.shared::cta.b64 [%0], %1;" ::"r"(a), "r"(c) : "memory"); }
__device__ __forceinline__ void mbar_expect(uint32_t a, uint32_t bytes) { asm volatile("mbarrier.arrive.expect_tx.shared::cta.b64 _, [%0], %1;" ::"r"(a), "r"(bytes) : "memory"); }
__device__ __forceinline__ void mbar_arrive(uint32_t a) { asm volatile("mbarrier.arrive.shared::cta.b64 _, [%0];" ::"r"(a) : "memory"); }
__device__ __forceinline__ void mbar_wait(uint32_t a, uint32_t ph) {
  asm volatile("{\n.reg .pred p;\n.reg .u32 c;\nmov.u32 c, 0;\nLW:\nmbarrier.try_wait.parity.shared::cta.b64 p, [%0], %1, %2;\n@p bra LD;\n"
               "add.u32 c, c, 1;\nsetp.lt.u32 p, c, 1048576;\n@p bra LW;\nLD:\n}" ::"r"(a), "r"(ph), "r"(20000u) : "memory");
}
template <int NS> __device__ __forceinline__ void mbar_wait_lazy(uint32_t a, uint32_t ph) {
  asm volatile("{\n.reg .pred p;\n.reg .u32 c;\nmov.u32 c, 0;\nLW:\nmbarrier.test_wait.parity.shared::cta.b64 p, [%0], %1;\n@p bra LD;\n"
               "nanosleep.u32 %2;\nadd.u32 c, c, 1;\nsetp.lt.u32 p, c, 4194304;\n@p bra LW;\nLD:\n}" ::"r"(a), "r"(ph), "n"(NS) : "memory");
}
__device__ __forceinline__ void tma2d(uint32_t dst, const CUtensorMap* m, int c0, int c1, uint32_t bar) {
  asm volatile("cp.async.bulk.tensor.2d.shared::cluster.global.mbarrier::complete_tx::bytes [%0], [%1, {%3,%4}], [%2];" ::"r"(dst), "l"(m), "r"(bar), "r"(c0), "r"(c1) : "memory");
}
__device__ __forceinline__ void tma3d(uint32_t dst, const CUtensorMap* m, int c0, int c1, int c2, uint32_t bar) {
  asm volatile("cp.async.bulk.tensor.3d.shared::cluster.global.mbarrier::complete_tx::bytes [%0], [%1, {%3,%4,%5}], [%2];" ::"r"(dst), "l"(m), "r"(bar), "r"(c0), "r"(c1), "r"(c2) : "memory");
}
__device__ __forceinline__ uint64_t mkdesc(uint32_t addr, uint32_t lbo, uint32_t sbo, uint32_t sw) {
  return (uint64_t)((addr & 0x3FFFF) >> 4) | ((uint64_t)(lbo >> 4) << 16) | ((uint64_t)(sbo >> 4) << 32) | ((uint64_t)sw << 62);
}
__device__ __forceinline__ void wg_fence() { asm volatile("wgmma.fence.sync.aligned;" ::: "memory"); }
__device__ __forceinline__ void wg_commit() { asm volatile("wgmma.commit_group.sync.aligned;" ::: "memory"); }
template <int N> __device__ __forceinline__ void wg_wait() { asm volatile("wgmma.wait_group.sync.aligned %0;" ::"n"(N) : "memory"); }
__device__ __forceinline__ void zero_reg(float& x) { asm volatile("mov.f32 %0, 0f00000000;" : "=f"(x)); }
__device__ __forceinline__ void movf(float& d, float s) { asm volatile("mov.f32 %0, %1;" : "=f"(d) : "f"(s)); }
__device__ __forceinline__ void bar_sync(int id, int n) { asm volatile("bar.sync %0, %1;" ::"r"(id), "r"(n) : "memory"); }
__device__ __forceinline__ void fence_async() { asm volatile("fence.proxy.async.shared::cta;" ::: "memory"); }
__device__ __forceinline__ uint32_t pack_bf16(float lo, float hi) {
  uint32_t r;
  asm("cvt.rn.bf16x2.f32 %0, %1, %2;" : "=r"(r) : "f"(hi), "f"(lo));
  return r;
}
__device__ __forceinline__ uint32_t hmul2_bf16(uint32_t a, uint32_t b) {
  uint32_t r;
  asm("mul.rn.bf16x2 %0, %1, %2;" : "=r"(r) : "r"(a), "r"(b));
  return r;
}
__device__ __forceinline__ uint32_t hadd2_bf16(uint32_t a, uint32_t b) {
  uint32_t r;
  asm("add.rn.bf16x2 %0, %1, %2;" : "=r"(r) : "r"(a), "r"(b));
  return r;
}
__device__ __forceinline__ float bf_lo(uint32_t v) { return __uint_as_float(v << 16); }
__device__ __forceinline__ float bf_hi(uint32_t v) { return __uint_as_float(v & 0xFFFF0000u); }
__device__ __forceinline__ float bf16r(float x) { return __bfloat162float(__float2bfloat16_rn(x)); }
__device__ __forceinline__ float ldbf(const __nv_bfloat16* p) { return __bfloat162float(*p); }
__device__ __forceinline__ uint32_t ld_acquire(const uint32_t* p) {
  uint32_t v;
  asm volatile("ld.acquire.gpu.global.u32 %0, [%1];" : "=r"(v) : "l"(p) : "memory");
  return v;
}
__device__ __forceinline__ void st_release(uint32_t* p, uint32_t v) { asm volatile("st.release.gpu.global.u32 [%0], %1;" ::"l"(p), "r"(v) : "memory"); }
__device__ __forceinline__ uint4 ld_cg4(const uint4* p) {
  uint4 v;
  asm volatile("ld.global.cg.v4.u32 {%0,%1,%2,%3}, [%4];" : "=r"(v.x), "=r"(v.y), "=r"(v.z), "=r"(v.w) : "l"(p) : "memory");
  return v;
}
__device__ __forceinline__ uint32_t ld_cg1(const void* p) {
  uint32_t v;
  asm volatile("ld.global.cg.u32 %0, [%1];" : "=r"(v) : "l"(p) : "memory");
  return v;
}
__device__ __forceinline__ uint32_t lds32(uint32_t a) {
  uint32_t v;
  asm volatile("ld.shared.u32 %0, [%1];" : "=r"(v) : "r"(a) : "memory");
  return v;
}
__device__ __forceinline__ void ldsm4(uint32_t (&r)[4], uint32_t a) {
  asm volatile("ldmatrix.sync.aligned.m8n8.x4.shared.b16 {%0,%1,%2,%3}, [%4];" : "=r"(r[0]), "=r"(r[1]), "=r"(r[2]), "=r"(r[3]) : "r"(a) : "memory");
}
__device__ __forceinline__ uint32_t pack_f16(float lo, float hi) {
  uint32_t r;
  asm("cvt.rn.f16x2.f32 %0, %1, %2;" : "=r"(r) : "f"(hi), "f"(lo));
  return r;
}

__device__ __forceinline__ void wgmma_ss_n256(float (&d)[128], uint64_t da, uint64_t db) {
  asm volatile("wgmma.mma_async.sync.aligned.m64n256k16.f32.bf16.bf16 {%0, %1, %2, %3, %4, %5, %6, %7, %8, %9, %10, %11, %12, %13, %14, %15, %16, %17, %18, %19, %20, %21, %22, %23, %24, %25, %26, %27, %28, %29, %30, %31, %32, %33, %34, %35, %36, %37, %38, %39, %40, %41, %42, %43, %44, %45, %46, %47, %48, %49, %50, %51, %52, %53, %54, %55, %56, %57, %58, %59, %60, %61, %62, %63, %64, %65, %66, %67, %68, %69, %70, %71, %72, %73, %74, %75, %76, %77, %78, %79, %80, %81, %82, %83, %84, %85, %86, %87, %88, %89, %90, %91, %92, %93, %94, %95, %96, %97, %98, %99, %100, %101, %102, %103, %104, %105, %106, %107, %108, %109, %110, %111, %112, %113, %114, %115, %116, %117, %118, %119, %120, %121, %122, %123, %124, %125, %126, %127}, %128, %129, 1, 1, 1, 0, 1;"
    : "+f"(d[0]), "+f"(d[1]), "+f"(d[2]), "+f"(d[3]), "+f"(d[4]), "+f"(d[5]), "+f"(d[6]), "+f"(d[7]), "+f"(d[8]), "+f"(d[9]), "+f"(d[10]), "+f"(d[11]), "+f"(d[12]), "+f"(d[13]), "+f"(d[14]), "+f"(d[15]), "+f"(d[16]), "+f"(d[17]), "+f"(d[18]), "+f"(d[19]), "+f"(d[20]), "+f"(d[21]), "+f"(d[22]), "+f"(d[23]), "+f"(d[24]), "+f"(d[25]), "+f"(d[26]), "+f"(d[27]), "+f"(d[28]), "+f"(d[29]), "+f"(d[30]), "+f"(d[31]), "+f"(d[32]), "+f"(d[33]), "+f"(d[34]), "+f"(d[35]), "+f"(d[36]), "+f"(d[37]), "+f"(d[38]), "+f"(d[39]), "+f"(d[40]), "+f"(d[41]), "+f"(d[42]), "+f"(d[43]), "+f"(d[44]), "+f"(d[45]), "+f"(d[46]), "+f"(d[47]), "+f"(d[48]), "+f"(d[49]), "+f"(d[50]), "+f"(d[51]), "+f"(d[52]), "+f"(d[53]), "+f"(d[54]), "+f"(d[55]), "+f"(d[56]), "+f"(d[57]), "+f"(d[58]), "+f"(d[59]), "+f"(d[60]), "+f"(d[61]), "+f"(d[62]), "+f"(d[63]), "+f"(d[64]), "+f"(d[65]), "+f"(d[66]), "+f"(d[67]), "+f"(d[68]), "+f"(d[69]), "+f"(d[70]), "+f"(d[71]), "+f"(d[72]), "+f"(d[73]), "+f"(d[74]), "+f"(d[75]), "+f"(d[76]), "+f"(d[77]), "+f"(d[78]), "+f"(d[79]), "+f"(d[80]), "+f"(d[81]), "+f"(d[82]), "+f"(d[83]), "+f"(d[84]), "+f"(d[85]), "+f"(d[86]), "+f"(d[87]), "+f"(d[88]), "+f"(d[89]), "+f"(d[90]), "+f"(d[91]), "+f"(d[92]), "+f"(d[93]), "+f"(d[94]), "+f"(d[95]), "+f"(d[96]), "+f"(d[97]), "+f"(d[98]), "+f"(d[99]), "+f"(d[100]), "+f"(d[101]), "+f"(d[102]), "+f"(d[103]), "+f"(d[104]), "+f"(d[105]), "+f"(d[106]), "+f"(d[107]), "+f"(d[108]), "+f"(d[109]), "+f"(d[110]), "+f"(d[111]), "+f"(d[112]), "+f"(d[113]), "+f"(d[114]), "+f"(d[115]), "+f"(d[116]), "+f"(d[117]), "+f"(d[118]), "+f"(d[119]), "+f"(d[120]), "+f"(d[121]), "+f"(d[122]), "+f"(d[123]), "+f"(d[124]), "+f"(d[125]), "+f"(d[126]), "+f"(d[127]) : "l"(da), "l"(db));
}
__device__ __forceinline__ void wgmma_rs_n96(float (&d)[48], uint32_t a0, uint32_t a1, uint32_t a2, uint32_t a3, uint64_t db) {
  asm volatile("wgmma.mma_async.sync.aligned.m64n96k16.f32.bf16.bf16 {%0, %1, %2, %3, %4, %5, %6, %7, %8, %9, %10, %11, %12, %13, %14, %15, %16, %17, %18, %19, %20, %21, %22, %23, %24, %25, %26, %27, %28, %29, %30, %31, %32, %33, %34, %35, %36, %37, %38, %39, %40, %41, %42, %43, %44, %45, %46, %47}, {%48,%49,%50,%51}, %52, 1, 1, 1, 1;"
    : "+f"(d[0]), "+f"(d[1]), "+f"(d[2]), "+f"(d[3]), "+f"(d[4]), "+f"(d[5]), "+f"(d[6]), "+f"(d[7]), "+f"(d[8]), "+f"(d[9]), "+f"(d[10]), "+f"(d[11]), "+f"(d[12]), "+f"(d[13]), "+f"(d[14]), "+f"(d[15]), "+f"(d[16]), "+f"(d[17]), "+f"(d[18]), "+f"(d[19]), "+f"(d[20]), "+f"(d[21]), "+f"(d[22]), "+f"(d[23]), "+f"(d[24]), "+f"(d[25]), "+f"(d[26]), "+f"(d[27]), "+f"(d[28]), "+f"(d[29]), "+f"(d[30]), "+f"(d[31]), "+f"(d[32]), "+f"(d[33]), "+f"(d[34]), "+f"(d[35]), "+f"(d[36]), "+f"(d[37]), "+f"(d[38]), "+f"(d[39]), "+f"(d[40]), "+f"(d[41]), "+f"(d[42]), "+f"(d[43]), "+f"(d[44]), "+f"(d[45]), "+f"(d[46]), "+f"(d[47]) : "r"(a0), "r"(a1), "r"(a2), "r"(a3), "l"(db));
}
__device__ __forceinline__ void wgmma_rs_n64t(float (&d)[32], uint32_t a0, uint32_t a1, uint32_t a2, uint32_t a3, uint64_t db) {
  asm volatile("wgmma.mma_async.sync.aligned.m64n64k16.f32.bf16.bf16 {%0, %1, %2, %3, %4, %5, %6, %7, %8, %9, %10, %11, %12, %13, %14, %15, %16, %17, %18, %19, %20, %21, %22, %23, %24, %25, %26, %27, %28, %29, %30, %31}, {%32,%33,%34,%35}, %36, 1, 1, 1, 1;"
    : "+f"(d[0]), "+f"(d[1]), "+f"(d[2]), "+f"(d[3]), "+f"(d[4]), "+f"(d[5]), "+f"(d[6]), "+f"(d[7]), "+f"(d[8]), "+f"(d[9]), "+f"(d[10]), "+f"(d[11]), "+f"(d[12]), "+f"(d[13]), "+f"(d[14]), "+f"(d[15]), "+f"(d[16]), "+f"(d[17]), "+f"(d[18]), "+f"(d[19]), "+f"(d[20]), "+f"(d[21]), "+f"(d[22]), "+f"(d[23]), "+f"(d[24]), "+f"(d[25]), "+f"(d[26]), "+f"(d[27]), "+f"(d[28]), "+f"(d[29]), "+f"(d[30]), "+f"(d[31]) : "r"(a0), "r"(a1), "r"(a2), "r"(a3), "l"(db));
}
__device__ __forceinline__ void cw128z(float (&d)[64], uint32_t a0, uint32_t a1, uint32_t a2, uint32_t a3, uint64_t db) {
  asm volatile("{.reg .pred p; setp.ne.b32 p, 0, 0; wgmma.mma_async.sync.aligned.m64n128k16.f32.bf16.bf16 {%0, %1, %2, %3, %4, %5, %6, %7, %8, %9, %10, %11, %12, %13, %14, %15, %16, %17, %18, %19, %20, %21, %22, %23, %24, %25, %26, %27, %28, %29, %30, %31, %32, %33, %34, %35, %36, %37, %38, %39, %40, %41, %42, %43, %44, %45, %46, %47, %48, %49, %50, %51, %52, %53, %54, %55, %56, %57, %58, %59, %60, %61, %62, %63}, {%64,%65,%66,%67}, %68, p, 1, 1, 0;}"
    : "=f"(d[0]), "=f"(d[1]), "=f"(d[2]), "=f"(d[3]), "=f"(d[4]), "=f"(d[5]), "=f"(d[6]), "=f"(d[7]), "=f"(d[8]), "=f"(d[9]), "=f"(d[10]), "=f"(d[11]), "=f"(d[12]), "=f"(d[13]), "=f"(d[14]), "=f"(d[15]), "=f"(d[16]), "=f"(d[17]), "=f"(d[18]), "=f"(d[19]), "=f"(d[20]), "=f"(d[21]), "=f"(d[22]), "=f"(d[23]), "=f"(d[24]), "=f"(d[25]), "=f"(d[26]), "=f"(d[27]), "=f"(d[28]), "=f"(d[29]), "=f"(d[30]), "=f"(d[31]), "=f"(d[32]), "=f"(d[33]), "=f"(d[34]), "=f"(d[35]), "=f"(d[36]), "=f"(d[37]), "=f"(d[38]), "=f"(d[39]), "=f"(d[40]), "=f"(d[41]), "=f"(d[42]), "=f"(d[43]), "=f"(d[44]), "=f"(d[45]), "=f"(d[46]), "=f"(d[47]), "=f"(d[48]), "=f"(d[49]), "=f"(d[50]), "=f"(d[51]), "=f"(d[52]), "=f"(d[53]), "=f"(d[54]), "=f"(d[55]), "=f"(d[56]), "=f"(d[57]), "=f"(d[58]), "=f"(d[59]), "=f"(d[60]), "=f"(d[61]), "=f"(d[62]), "=f"(d[63]) : "r"(a0), "r"(a1), "r"(a2), "r"(a3), "l"(db));
}
__device__ __forceinline__ void cw128(float (&d)[64], uint32_t a0, uint32_t a1, uint32_t a2, uint32_t a3, uint64_t db) {
  asm volatile("wgmma.mma_async.sync.aligned.m64n128k16.f32.bf16.bf16 {%0, %1, %2, %3, %4, %5, %6, %7, %8, %9, %10, %11, %12, %13, %14, %15, %16, %17, %18, %19, %20, %21, %22, %23, %24, %25, %26, %27, %28, %29, %30, %31, %32, %33, %34, %35, %36, %37, %38, %39, %40, %41, %42, %43, %44, %45, %46, %47, %48, %49, %50, %51, %52, %53, %54, %55, %56, %57, %58, %59, %60, %61, %62, %63}, {%64,%65,%66,%67}, %68, 1, 1, 1, 0;"
    : "+f"(d[0]), "+f"(d[1]), "+f"(d[2]), "+f"(d[3]), "+f"(d[4]), "+f"(d[5]), "+f"(d[6]), "+f"(d[7]), "+f"(d[8]), "+f"(d[9]), "+f"(d[10]), "+f"(d[11]), "+f"(d[12]), "+f"(d[13]), "+f"(d[14]), "+f"(d[15]), "+f"(d[16]), "+f"(d[17]), "+f"(d[18]), "+f"(d[19]), "+f"(d[20]), "+f"(d[21]), "+f"(d[22]), "+f"(d[23]), "+f"(d[24]), "+f"(d[25]), "+f"(d[26]), "+f"(d[27]), "+f"(d[28]), "+f"(d[29]), "+f"(d[30]), "+f"(d[31]), "+f"(d[32]), "+f"(d[33]), "+f"(d[34]), "+f"(d[35]), "+f"(d[36]), "+f"(d[37]), "+f"(d[38]), "+f"(d[39]), "+f"(d[40]), "+f"(d[41]), "+f"(d[42]), "+f"(d[43]), "+f"(d[44]), "+f"(d[45]), "+f"(d[46]), "+f"(d[47]), "+f"(d[48]), "+f"(d[49]), "+f"(d[50]), "+f"(d[51]), "+f"(d[52]), "+f"(d[53]), "+f"(d[54]), "+f"(d[55]), "+f"(d[56]), "+f"(d[57]), "+f"(d[58]), "+f"(d[59]), "+f"(d[60]), "+f"(d[61]), "+f"(d[62]), "+f"(d[63]) : "r"(a0), "r"(a1), "r"(a2), "r"(a3), "l"(db));
}
__device__ __forceinline__ void cw96(float (&d)[48], uint32_t a0, uint32_t a1, uint32_t a2, uint32_t a3, uint64_t db) {
  asm volatile("wgmma.mma_async.sync.aligned.m64n96k16.f32.bf16.bf16 {%0, %1, %2, %3, %4, %5, %6, %7, %8, %9, %10, %11, %12, %13, %14, %15, %16, %17, %18, %19, %20, %21, %22, %23, %24, %25, %26, %27, %28, %29, %30, %31, %32, %33, %34, %35, %36, %37, %38, %39, %40, %41, %42, %43, %44, %45, %46, %47}, {%48,%49,%50,%51}, %52, 1, 1, 1, 0;"
    : "+f"(d[0]), "+f"(d[1]), "+f"(d[2]), "+f"(d[3]), "+f"(d[4]), "+f"(d[5]), "+f"(d[6]), "+f"(d[7]), "+f"(d[8]), "+f"(d[9]), "+f"(d[10]), "+f"(d[11]), "+f"(d[12]), "+f"(d[13]), "+f"(d[14]), "+f"(d[15]), "+f"(d[16]), "+f"(d[17]), "+f"(d[18]), "+f"(d[19]), "+f"(d[20]), "+f"(d[21]), "+f"(d[22]), "+f"(d[23]), "+f"(d[24]), "+f"(d[25]), "+f"(d[26]), "+f"(d[27]), "+f"(d[28]), "+f"(d[29]), "+f"(d[30]), "+f"(d[31]), "+f"(d[32]), "+f"(d[33]), "+f"(d[34]), "+f"(d[35]), "+f"(d[36]), "+f"(d[37]), "+f"(d[38]), "+f"(d[39]), "+f"(d[40]), "+f"(d[41]), "+f"(d[42]), "+f"(d[43]), "+f"(d[44]), "+f"(d[45]), "+f"(d[46]), "+f"(d[47]) : "r"(a0), "r"(a1), "r"(a2), "r"(a3), "l"(db));
}
__device__ __forceinline__ void cw64(float (&d)[32], uint32_t a0, uint32_t a1, uint32_t a2, uint32_t a3, uint64_t db) {
  asm volatile("wgmma.mma_async.sync.aligned.m64n64k16.f32.bf16.bf16 {%0, %1, %2, %3, %4, %5, %6, %7, %8, %9, %10, %11, %12, %13, %14, %15, %16, %17, %18, %19, %20, %21, %22, %23, %24, %25, %26, %27, %28, %29, %30, %31}, {%32,%33,%34,%35}, %36, 1, 1, 1, 0;"
    : "+f"(d[0]), "+f"(d[1]), "+f"(d[2]), "+f"(d[3]), "+f"(d[4]), "+f"(d[5]), "+f"(d[6]), "+f"(d[7]), "+f"(d[8]), "+f"(d[9]), "+f"(d[10]), "+f"(d[11]), "+f"(d[12]), "+f"(d[13]), "+f"(d[14]), "+f"(d[15]), "+f"(d[16]), "+f"(d[17]), "+f"(d[18]), "+f"(d[19]), "+f"(d[20]), "+f"(d[21]), "+f"(d[22]), "+f"(d[23]), "+f"(d[24]), "+f"(d[25]), "+f"(d[26]), "+f"(d[27]), "+f"(d[28]), "+f"(d[29]), "+f"(d[30]), "+f"(d[31]) : "r"(a0), "r"(a1), "r"(a2), "r"(a3), "l"(db));
}
__device__ __forceinline__ void cw32(float (&d)[16], uint32_t a0, uint32_t a1, uint32_t a2, uint32_t a3, uint64_t db) {
  asm volatile("wgmma.mma_async.sync.aligned.m64n32k16.f32.bf16.bf16 {%0, %1, %2, %3, %4, %5, %6, %7, %8, %9, %10, %11, %12, %13, %14, %15}, {%16,%17,%18,%19}, %20, 1, 1, 1, 0;"
    : "+f"(d[0]), "+f"(d[1]), "+f"(d[2]), "+f"(d[3]), "+f"(d[4]), "+f"(d[5]), "+f"(d[6]), "+f"(d[7]), "+f"(d[8]), "+f"(d[9]), "+f"(d[10]), "+f"(d[11]), "+f"(d[12]), "+f"(d[13]), "+f"(d[14]), "+f"(d[15]) : "r"(a0), "r"(a1), "r"(a2), "r"(a3), "l"(db));
}


struct cpx { float r, i; };
__device__ __forceinline__ cpx cmul(cpx a, cpx b) { return {fmaf(a.r, b.r, -a.i * b.i), fmaf(a.r, b.i, a.i * b.r)}; }
__device__ __forceinline__ cpx csqr(cpx a) { return {fmaf(a.r, a.r, -a.i * a.i), (a.r * a.i) * 2.f}; }
__device__ __forceinline__ cpx cmulc(cpx a, cpx b) { return {fmaf(a.r, b.r, -a.i * b.i), fmaf(-a.r, b.i, -a.i * b.r)}; }
__device__ __forceinline__ cpx cexp_fast(float re, float im) {
  float e;
  asm("ex2.approx.ftz.f32 %0, %1;" : "=f"(e) : "f"(re * 1.4426950408889634f));
  float k = rintf(im * 0.15915494309189535f);
  float r = fmaf(k, -6.2831854820251465f, im);
  r = fmaf(k, 1.7484555314695172e-07f, r);
  float s, c;
  asm("sin.approx.f32 %0, %1;" : "=f"(s) : "f"(r));
  asm("cos.approx.f32 %0, %1;" : "=f"(c) : "f"(r));
  return {e * c, e * s};
}

struct KOps { uint32_t xa[5], xb[5], y[4]; };
__device__ __forceinline__ void kgen_ops(KOps& o, const float4 pr, const float2 qq, const float gf) {
  const cpx C = {pr.z, pr.w};
  const cpx Q = {qq.x, qq.y};
  const cpx V0 = cexp_fast(pr.x * gf, pr.y * gf);
  const cpx V1 = csqr(V0), V2 = csqr(V1), V3 = csqr(V2);
  const cpx Y0 = cmulc(C, V0), Y1 = cmulc(C, V1), Y2 = cmulc(C, V2), Y3 = cmulc(C, V3);
  o.y[0] = pack_f16(Y0.r, Y0.i); o.y[1] = pack_f16(Y1.r, Y1.i); o.y[2] = pack_f16(Y2.r, Y2.i); o.y[3] = pack_f16(Y3.r, Y3.i);
  const cpx Xb = cmul(V3, Q);
  cpx Xc = cmul(Xb, Q), Xd = cmul(Xc, Q);
  o.xa[0] = pack_f16(V3.r, V3.i); o.xb[0] = pack_f16(Xb.r, Xb.i);
  o.xa[1] = pack_f16(Xc.r, Xc.i); o.xb[1] = pack_f16(Xd.r, Xd.i);
#pragma unroll
  for (int k = 2; k < 5; k++) {
    Xc = csqr(Xc); Xd = csqr(Xd);
    o.xa[k] = pack_f16(Xc.r, Xc.i); o.xb[k] = pack_f16(Xd.r, Xd.i);
  }
}
__device__ __forceinline__ void kgen_mma(float (&T)[5][4], const KOps& a, const KOps& b) {
  asm("mma.sync.aligned.m16n8k16.row.col.f32.f16.f16.f32 {%0,%1,%2,%3}, {%20,%21,%22,%23}, {%40,%41}, {%0,%1,%2,%3};\n"
      "mma.sync.aligned.m16n8k16.row.col.f32.f16.f16.f32 {%4,%5,%6,%7}, {%24,%25,%26,%27}, {%40,%41}, {%4,%5,%6,%7};\n"
      "mma.sync.aligned.m16n8k16.row.col.f32.f16.f16.f32 {%8,%9,%10,%11}, {%28,%29,%30,%31}, {%42,%43}, {%8,%9,%10,%11};\n"
      "mma.sync.aligned.m16n8k16.row.col.f32.f16.f16.f32 {%12,%13,%14,%15}, {%32,%33,%34,%35}, {%44,%45}, {%12,%13,%14,%15};\n"
      "mma.sync.aligned.m16n8k16.row.col.f32.f16.f16.f32 {%16,%17,%18,%19}, {%36,%37,%38,%39}, {%46,%47}, {%16,%17,%18,%19};\n"
      : "+f"(T[0][0]), "+f"(T[0][1]), "+f"(T[0][2]), "+f"(T[0][3]), "+f"(T[1][0]), "+f"(T[1][1]), "+f"(T[1][2]), "+f"(T[1][3]),
        "+f"(T[2][0]), "+f"(T[2][1]), "+f"(T[2][2]), "+f"(T[2][3]), "+f"(T[3][0]), "+f"(T[3][1]), "+f"(T[3][2]), "+f"(T[3][3]),
        "+f"(T[4][0]), "+f"(T[4][1]), "+f"(T[4][2]), "+f"(T[4][3])
      : "r"(a.xa[0]), "r"(a.xb[0]), "r"(b.xa[0]), "r"(b.xb[0]), "r"(a.xa[1]), "r"(a.xb[1]), "r"(b.xa[1]), "r"(b.xb[1]),
        "r"(a.xa[2]), "r"(a.xb[2]), "r"(b.xa[2]), "r"(b.xb[2]), "r"(a.xa[3]), "r"(a.xb[3]), "r"(b.xa[3]), "r"(b.xb[3]),
        "r"(a.xa[4]), "r"(a.xb[4]), "r"(b.xa[4]), "r"(b.xb[4]),
        "r"(a.y[0]), "r"(b.y[0]), "r"(a.y[1]), "r"(b.y[1]), "r"(a.y[2]), "r"(b.y[2]), "r"(a.y[3]), "r"(b.y[3]));
}

template <int J0> __device__ __forceinline__ void conv_load4(uint32_t (&f)[4][4], uint32_t ebase, uint32_t zero) {
#pragma unroll
  for (int t = 0; t < 4; t++) {
    f[t][0] = lds32(ebase + (J0 + t) * 128);
    f[t][1] = lds32(ebase + (J0 + t) * 128 + 16);
    f[t][3] = lds32(ebase + (J0 + t) * 128 + 32);
  }
#pragma unroll
  for (int t = 0; t < 4; t++)
    asm volatile("xor.b32 %0, %1, %2;" : "=r"(f[t][2]) : "r"(f[t][1]), "r"(zero));
}
#define CONV_GRP(FN, ACC, J0, F)                                                             \
  wg_fence();                                                                                \
  FN(ACC, F[0][0], F[0][1], F[0][2], F[0][3], de + 4 * (J0));                                \
  FN(ACC, F[1][0], F[1][1], F[1][2], F[1][3], de + 4 * (J0 + 1));                            \
  FN(ACC, F[2][0], F[2][1], F[2][2], F[2][3], de + 4 * (J0 + 2));                            \
  FN(ACC, F[3][0], F[3][1], F[3][2], F[3][3], de + 4 * (J0 + 3));                            \
  wg_commit();
#define CONV_STAGE(ACC, M0)                                                                  \
  _Pragma("unroll") for (int m = (M0); m < (M0) + 4; m++) {                                  \
    *(float2*)(Sw + 8 * m) = make_float2(ACC[4 * m], ACC[4 * m + 1]);                        \
    *(float2*)(Sw + 8 * S_PITCH + 8 * m) = make_float2(ACC[4 * m + 2], ACC[4 * m + 3]);      \
  }
#define CONV_CHANNEL(PRE, MID1, MID2)                                                                    \
  {                                                                                          \
    float a128[64], a96[48], a64[32], a32[16];                                               \
    wg_fence();                                                                              \
    cw128z(a128, fa[0][0], fa[0][1], fa[0][2], fa[0][3], de);                                \
    cw128(a128, fa[1][0], fa[1][1], fa[1][2], fa[1][3], de + 4);                             \
    cw128(a128, fa[2][0], fa[2][1], fa[2][2], fa[2][3], de + 8);                             \
    cw128(a128, fa[3][0], fa[3][1], fa[3][2], fa[3][3], de + 12);                            \
    wg_commit();                                                                             \
    CONV_GRP(cw128, a128, 4, fb)                                                             \
    MID1                                                                                     \
    wg_wait<1>(); conv_load4<8>(fa, ebase, zero);                                            \
    wg_wait<0>(); conv_load4<12>(fb, ebase, zero);                                           \
    _Pragma("unroll") for (int i = 0; i < 48; i++) movf(a96[i], a128[i]);                       \
    CONV_GRP(cw96, a96, 8, fa)                                                               \
    CONV_GRP(cw96, a96, 12, fb)                                                              \
    MID2                                                                                     \
    PRE                                                                                      \
    CONV_STAGE(a128, 12)                                                                     \
    wg_wait<1>(); conv_load4<16>(fa, ebase, zero);                                           \
    wg_wait<0>(); conv_load4<20>(fb, ebase, zero);                                           \
    _Pragma("unroll") for (int i = 0; i < 32; i++) movf(a64[i], a96[i]);                        \
    CONV_GRP(cw64, a64, 16, fa)                                                              \
    CONV_GRP(cw64, a64, 20, fb)                                                              \
    CONV_STAGE(a96, 8)                                                                       \
    wg_wait<1>(); conv_load4<24>(fa, ebase, zero);                                           \
    wg_wait<0>(); conv_load4<28>(fb, ebase, zero);                                           \
    _Pragma("unroll") for (int i = 0; i < 16; i++) movf(a32[i], a64[i]);                        \
    CONV_GRP(cw32, a32, 24, fa)                                                              \
    CONV_GRP(cw32, a32, 28, fb)                                                              \
    CONV_STAGE(a64, 4)                                                                       \
    load_u(ch);                                                                              \
    wg_wait<0>();                                                                            \
    CONV_STAGE(a32, 0)                                                                       \
  }

__device__ __forceinline__ int part_slot(int s, int v) {
  if (s == 6) return CV_E + 2 * v * E_CH;
  if (s == 5) return v ? (SM_PR - SM_X) : (CV_S + 2 * S_WG);
  return CV_S + v * S_WG + (s & 3) * 8192;
}
template <int V> struct IC { static constexpr int value = V; };

struct Params {
  const __nv_bfloat16* x;
  const __nv_bfloat16* log_A_real;
  const __nv_bfloat16* A_imag;
  const __nv_bfloat16* C_real;
  const __nv_bfloat16* C_imag;
  const __nv_bfloat16* log_dt;
  const __nv_bfloat16* D_skip;
  const __nv_bfloat16* gate_w;
  const __nv_bfloat16* w_gate;
  const __nv_bfloat16* w_up;
  const __nv_bfloat16* w_down;
  __nv_bfloat16* out;
};

struct Maps {
  CUtensorMap X, Wg, Wu, Wg3[2], Wu3[2], Wd, AT;
};

__device__ __forceinline__ uint32_t ld_epoch() { return *(volatile uint32_t*)&g_epoch; }
__device__ __forceinline__ uint32_t dup_lo(uint32_t w) { return __byte_perm(w, w, 0x1010); }
__device__ __forceinline__ uint32_t dup_hi(uint32_t w) { return __byte_perm(w, w, 0x3232); }

__global__ void __launch_bounds__(NTHREADS, 1)
fused_kernel(const __grid_constant__ Maps M, const Params P) {
  extern __shared__ __align__(1024) uint8_t smem[];
  const uint32_t sb = smem_u32(smem);
  const uint32_t bars = sb + SM_BAR;
  const int tid = threadIdx.x;
  const int warp = __shfl_sync(0xffffffffu, tid >> 5, 0), lane = tid & 31;
  const int b = blockIdx.x;
  const int cl = b >> 1;
  const int jf = cl & 7;
  const int it_ = ((cl >> 3) << 1) | (b & 1);
  const int d0 = b * 4;

  const int kch = warp / 3;
  const int kpart = (warp - 3 * kch + (kch < 2 ? kch : 2)) % 3;
  const int kk0 = kpart == 0 ? 0 : (kpart == 1 ? 6 : 11), nks = kpart == 0 ? 6 : 5;
  uint32_t pw0[2], pw1[2], pldt;
  {
    unsigned short raw[9];
    int n0 = 8 * kk0 + lane, n1 = n0 + 32;
    n0 = (d0 + kch) * NS_ + n0;
    n1 = (d0 + kch) * NS_ + (n1 < NS_ ? n1 : NS_ - 1);
    asm volatile("ld.global.nc.u16 %0, [%9];\n\tld.global.nc.u16 %1, [%10];\n\tld.global.nc.u16 %2, [%11];\n\t"
                 "ld.global.nc.u16 %3, [%12];\n\tld.global.nc.u16 %4, [%13];\n\tld.global.nc.u16 %5, [%14];\n\t"
                 "ld.global.nc.u16 %6, [%15];\n\tld.global.nc.u16 %7, [%16];\n\tld.global.nc.u16 %8, [%17];"
                 : "=h"(raw[0]), "=h"(raw[1]), "=h"(raw[2]), "=h"(raw[3]), "=h"(raw[4]), "=h"(raw[5]), "=h"(raw[6]), "=h"(raw[7]), "=h"(raw[8])
                 : "l"(P.log_A_real + n0), "l"(P.A_imag + n0), "l"(P.C_real + n0), "l"(P.C_imag + n0),
                   "l"(P.log_A_real + n1), "l"(P.A_imag + n1), "l"(P.C_real + n1), "l"(P.C_imag + n1), "l"(P.log_dt + d0 + kch));
  if (lane == 0) {
    if (warp == 8) {
      mbar_init(bars + 8 * (B_FULL + 0), 1); mbar_init(bars + 8 * (B_FULL + 2), 1); mbar_init(bars + 8 * (B_FULL + 4), 1);
      mbar_init(bars + 8 * (B_XFULL + 0), 1); mbar_init(bars + 8 * (B_XFULL + 2), 1); mbar_init(bars + 8 * (B_XFULL + 4), 1);
    } else if (warp == 9) {
      mbar_init(bars + 8 * (B_FULL + 1), 1); mbar_init(bars + 8 * (B_FULL + 3), 1);
      mbar_init(bars + 8 * (B_XFULL + 1), 1); mbar_init(bars + 8 * (B_XFULL + 3), 1); mbar_init(bars + 8 * (B_XFULL + 5), 1);
    } else {
      const int wi = warp < 8 ? warp : warp - 2;
#pragma unroll
      for (int r = 0; r < 5; r++) {
        int i = wi + 10 * r + 5;
        if (i >= B_XFULL) i += 6;
        uint32_t cnt = 1;
        if ((i >= B_EMPTY && i < B_EMPTY + 5) || (i >= B_XFREE && i < B_XFREE + 8) || (i >= B_SENT && i < B_SENT + 8) || i == B_ADONE || i == B_ADONE + 1) cnt = 8;
        if (i == B_RRDY || i == B_KSUM) cnt = 2;
        if (i == B_GOT) cnt = 7;
        mbar_init(bars + 8 * i, cnt);
      }
    }
    asm volatile("fence.mbarrier_init.release.cluster;" ::: "memory");
  }
  __syncwarp();
    pw0[0] = (uint32_t)raw[0] | ((uint32_t)raw[1] << 16); pw1[0] = (uint32_t)raw[2] | ((uint32_t)raw[3] << 16);
    pw0[1] = (uint32_t)raw[4] | ((uint32_t)raw[5] << 16); pw1[1] = (uint32_t)raw[6] | ((uint32_t)raw[7] << 16);
    pldt = raw[8];
  }

  auto issue_stage = [&](int s, int slot) {
    const uint32_t dst = sb + SM_RING + slot * 16384;
    const uint32_t fb = bars + 8 * (B_FULL + slot);
    if (s < 32) {
      const int f0 = jf * 224 + ((s >> 4) << 7);
      const int k0 = (s & 15) * 32;
      mbar_expect(fb, 16384);
      if (jf == 7 && s >= 16) {
        tma2d(dst, &M.Wg, f0, k0, fb);
        tma2d(dst + 4096, &M.Wg, f0 + 64, k0, fb);
        tma2d(dst + 8192, &M.Wu, f0, k0, fb);
        tma2d(dst + 12288, &M.Wu, f0 + 64, k0, fb);
      } else {
        tma3d(dst, &M.Wg3[jf & 1], 0, k0, f0 >> 6, fb);
        tma3d(dst + 8192, &M.Wu3[jf & 1], 0, k0, f0 >> 6, fb);
      }
    } else {
      const int s2 = s - 32;
      const int p = (jf + 1 + (s2 >> 1)) & 7;
      mbar_expect(fb, 14336);
      tma2d(dst, &M.Wd, p * 64, jf * 224 + (s2 & 1) * 112, fb);
    }
  };
  auto issue_x = [&](int kb) {
    mbar_expect(bars + 8 * (B_XFULL + kb), 16384);
    tma2d(sb + SM_X + kb * 16384, &M.X, kb * 64, it_ * 128, bars + 8 * (B_XFULL + kb));
  };
  {
    const int g = lane >> 2, q = lane & 3;
    const float dtf = bf16r(expf(bf_lo(pldt)));
    const int pro = kch * 128 + 8 * kk0;
    float4* prm = (float4*)(smem + SM_PR) + pro;
    float2* prq = (float2*)(smem + SM_PR + 512 * 16) + pro;
    const bool valid1 = lane + 32 < 8 * nks;
    float m0 = fmaxf(fmaxf(fabsf(bf_lo(pw1[0])), fabsf(bf_hi(pw1[0]))), fmaxf(fabsf(bf_lo(pw1[1])), fabsf(bf_hi(pw1[1])))) * dtf;
#pragma unroll
    for (int o = 16; o > 0; o >>= 1) m0 = fmaxf(m0, __shfl_xor_sync(0xffffffffu, m0, o));
    if (m0 >= 0.f || m0 != m0) {
      if (tid == 256) {
        issue_x(0); issue_stage(0, 0); issue_stage(2, 2); issue_x(2); issue_stage(4, 4); issue_x(4);
      } else if (tid == 288) {
        issue_stage(1, 1); issue_x(1); issue_stage(3, 3); issue_x(3); issue_x(5);
      }
    }
    __syncwarp();
    const uint32_t e0 = min(max(__float_as_uint(m0) >> 23, 1u), 253u);
    const float sc = __uint_as_float((254u - e0) << 23);
    const float us = 2.f * __uint_as_float(e0 << 23);
    float pe = 0.f;
#pragma unroll
    for (int r = 0; r < 2; r++) {
      float4 v;
      v.x = -bf16r(expf(bf_lo(pw0[r]))) * dtf;
      v.y = bf_hi(pw0[r]) * dtf;
      v.z = bf_lo(pw1[r]) * dtf * sc;
      v.w = bf_hi(pw1[r]) * dtf * sc;
      const cpx Q = cexp_fast(v.x * 64.f, v.y * 64.f);
      const cpx We = cexp_fast(v.x * 2048.f, v.y * 2048.f);
      if (r == 0 || valid1) {
        pe += v.z * We.r - v.w * We.i;
        prm[lane + 32 * r] = v;
        prq[lane + 32 * r] = make_float2(Q.r, Q.i);
      }
    }
#pragma unroll
    for (int o = 16; o > 0; o >>= 1) pe += __shfl_xor_sync(0xffffffffu, pe, o);
    __syncwarp();
    float T[5][4];
#pragma unroll
    for (int i = 0; i < 20; i++) T[i >> 2][i & 3] = 0.f;
    const float gf = (float)g;
#pragma unroll 1
    for (int ks = 0; ks < nks; ks++) {
      KOps o1, o2;
      kgen_ops(o1, prm[8 * ks + q], prq[8 * ks + q], gf);
      kgen_ops(o2, prm[8 * ks + 4 + q], prq[8 * ks + 4 + q], gf);
      kgen_mma(T, o1, o2);
    }
    float* kp = (float*)(smem + SM_X + 6 * 16384) + warp * KC_STRIDE + 8 * g + 2 * q;
#pragma unroll
    for (int k = 0; k < 5; k++) {
      *(float2*)(kp + 128 * k) = make_float2(T[k][0] * us, T[k][1] * us);
      *(float2*)(kp + 128 * k + 64) = make_float2(T[k][2] * us, T[k][3] * us);
    }
    if (lane == 0) { kp[640] = pe * us; kp[641] = 0.f; }
  }
  __syncthreads();

  if (warp >= 8) {
    asm volatile("setmaxnreg.dec.sync.aligned.u32 104;");
    if (warp < 10) {
      if (lane == 0) {
        int slot = (warp == 8) ? 1 : 0;
        uint32_t ph = 0;
#pragma unroll 1
        for (int s = (warp == 8) ? 6 : 5; s < 48; s += 2) {
          if (s == 10) { mbar_wait(bars + 8 * B_KSUM, 0); issue_x(6); issue_x(7); }
          mbar_wait(bars + 8 * (B_EMPTY + slot), ph);
          issue_stage(s, slot);
          slot += 2;
          if (slot >= 5) { slot -= 5; ph ^= 1; }
        }
      }
      __syncwarp();
      {
        const uint4 gw0 = *(const uint4*)(P.gate_w + lane * 16);
        const uint4 gw1 = *(const uint4*)(P.gate_w + lane * 16 + 8);
        uint4 xa[8], xb[8];
#pragma unroll
        for (int i = 0; i < 8; i++) {
          xa[i] = *(const uint4*)(P.x + (b * 16 + (warp - 8) * 8 + i) * D_ + lane * 16);
          xb[i] = *(const uint4*)(P.x + (b * 16 + (warp - 8) * 8 + i) * D_ + lane * 16 + 8);
        }
        float sg[8];
#pragma unroll
        for (int i = 0; i < 8; i++) {
          const uint32_t pr[8] = {hmul2_bf16(xa[i].x, gw0.x), hmul2_bf16(xa[i].y, gw0.y), hmul2_bf16(xa[i].z, gw0.z), hmul2_bf16(xa[i].w, gw0.w),
                                  hmul2_bf16(xb[i].x, gw1.x), hmul2_bf16(xb[i].y, gw1.y), hmul2_bf16(xb[i].z, gw1.z), hmul2_bf16(xb[i].w, gw1.w)};
          float s = 0.f;
#pragma unroll
          for (int k = 0; k < 8; k++) s += bf_lo(pr[k]) + bf_hi(pr[k]);
          sg[i] = s;
        }
#pragma unroll
        for (int o = 16; o > 0; o >>= 1) {
#pragma unroll
          for (int i = 0; i < 8; i++) sg[i] += __shfl_xor_sync(0xffffffffu, sg[i], o);
        }
        float z = sg[0];
#pragma unroll
        for (int i = 1; i < 8; i++) z = (lane == i) ? sg[i] : z;
        if (lane < 8) g_gate[b * 16 + (warp - 8) * 8 + lane] = bf16r(1.f / (1.f + expf(-bf16r(z))));
      }
      bar_sync(3, 64);
      if (tid == 288) asm volatile("red.release.gpu.global.add.u32 [%0], 1;" ::"l"(&g_done1) : "memory");
      if (warp == 8) {
        if (lane >= 1 && lane < 8) {
          const uint32_t tag = ld_epoch() + 1;
          const uint32_t* fp = g_flag + ((it_ * 8 + jf) * 8 + ((jf - lane) & 7));
          int itc = 0;
          while (ld_acquire(fp) != tag) { __nanosleep(100); if (++itc > SPIN_LIMIT) FAIL(-2, lane); }
          mbar_arrive(bars + 8 * B_GOT);
        }
      } else if (lane == 0) {
        const uint32_t tag = ld_epoch() + 1;
#pragma unroll 1
        for (int rnd = 0; rnd < 2; rnd++) {
          if (rnd == 1) {
            int itc = 0;
            while ((int)(ld_acquire(&g_done1) - (uint32_t)NCTA * tag) < 0) { if (++itc > SPIN_LIMIT) FAIL(-1, 0); }
            mbar_wait(bars + 8 * (B_ADONE + 1), 0);
          } else {
            mbar_wait_lazy<100>(bars + 8 * B_ADONE, 0);
          }
#pragma unroll
          for (int v = 0; v < 2; v++)
            asm volatile("cp.async.bulk.global.shared::cta.bulk_group [%0], [%1], %2;"
                         ::"l"(g_aT + (d0 + 2 * v + rnd) * L_), "r"(sb + SM_X + CV_R + (2 * v + rnd) * R_CH), "r"(4096) : "memory");
          asm volatile("cp.async.bulk.commit_group;" ::: "memory");
          asm volatile("cp.async.bulk.wait_group 0;" ::: "memory");
          asm volatile("fence.proxy.async.global;" ::: "memory");
          asm volatile("red.release.gpu.global.add.u32 [%0], 1;" ::"l"(g_cnt + 32 * (b >> 4)) : "memory");
        }
        {
          int itc = 0;
          while ((int)(ld_acquire(g_cnt + 32 * jf) - 32u * tag) < 0) { if (++itc > SPIN_LIMIT) FAIL(-3, 0); }
        }
        asm volatile("fence.proxy.async.global;" ::: "memory");
        mbar_expect(bars + 8 * B_ATILE, 16384);
        tma2d(sb + SM_AT, &M.AT, it_ * 128, jf * 64, bars + 8 * B_ATILE);
        tma2d(sb + SM_AT + 8192, &M.AT, it_ * 128 + 64, jf * 64, bars + 8 * B_ATILE);
      }
      __syncwarp();
    } else {
      const int w = warp - 10;
      const int wt = tid - 320;
      {
        const float2* kp = (const float2*)(smem + SM_X + 6 * 16384);
        uint32_t* kb = (uint32_t*)(smem + SM_KB);
#pragma unroll
        for (int ch = 0; ch < 4; ch++) {
#pragma unroll
          for (int i = 0; i < 6; i++) {
            const int o = wt + 64 * i;
            if (i < 5 || o < 321) {
              const float2 a0 = kp[(3 * ch) * (KC_STRIDE / 2) + o], a1 = kp[(3 * ch + 1) * (KC_STRIDE / 2) + o], a2 = kp[(3 * ch + 2) * (KC_STRIDE / 2) + o];
              kb[ch * (KC_STRIDE / 2) + o] = pack_bf16(a0.x + a1.x + a2.x, a0.y + a1.y + a2.y);
            }
          }
        }
      }
      fence_async();
      bar_sync(1, 64);
      if (lane == 0) mbar_arrive(bars + 8 * B_KSUM);
      {
        const uint32_t zz = *(volatile uint32_t*)&g_zero;
        uint2 ur[4][8];
#pragma unroll
        for (int i = 0; i < 4; i++) {
#pragma unroll
          for (int r = 0; r < 8; r++) {
            uint32_t ck;
            asm volatile("nanosleep.u32 90;\n\tmov.u32 %0, %%clock;" : "=r"(ck) :: "memory");
            asm volatile("ld.global.nc.v2.u32 {%0,%1}, [%2];" : "=r"(ur[i][r].x), "=r"(ur[i][r].y)
                         : "l"(P.x + ((wt + 64 * i) * 8 + r) * D_ + d0 + (ck & zz)));
          }
        }
        mbar_wait_lazy<200>(bars + 8 * (B_XFREE + 3), 0);
#pragma unroll
        for (int i = 0; i < 4; i++) {
          const int item = wt + 64 * i;
          const int c = item >> 1, hh = item & 1;
#pragma unroll
          for (int ch = 0; ch < 4; ch++) {
            uint32_t v[4];
#pragma unroll
            for (int k = 0; k < 4; k++) {
              const uint32_t lo = (ch < 2) ? ur[i][7 - 2 * k].x : ur[i][7 - 2 * k].y;
              const uint32_t hi = (ch < 2) ? ur[i][6 - 2 * k].x : ur[i][6 - 2 * k].y;
              v[k] = (ch & 1) ? __byte_perm(lo, hi, 0x7632) : __byte_perm(lo, hi, 0x5410);
            }
            *(uint4*)(smem + SM_X + CV_R + ch * R_CH + (1 - hh) * R_HALF + (127 - c) * 16) = make_uint4(v[0], v[1], v[2], v[3]);
          }
        }
        if (lane < 28) {
#pragma unroll
          for (int z = 0; z < 4; z++)
            *(uint4*)(smem + SM_X + CV_R + (4 * w + z) * R_HALF + (128 + lane) * 16) = make_uint4(0, 0, 0, 0);
        }
      }
      auto part_store = [&](int s) {
        mbar_wait_lazy<100>(bars + 8 * (B_SENT + s), 0);
        const int fi = (it_ * 8 + ((jf + 1 + s) & 7)) * 8 + jf;
#pragma unroll
        for (int v = 0; v < 2; v++)
          asm volatile("cp.async.bulk.global.shared::cta.bulk_group [%0], [%1], %2;"
                       ::"l"(g_part + (size_t)fi * 1024 + v * 512), "r"(sb + SM_X + part_slot(s, v)), "r"(8192) : "memory");
        asm volatile("cp.async.bulk.commit_group;" ::: "memory");
      };
      {
#pragma unroll 1
      for (int G = w; G < 8; G += 2) {
        const int n = 32 * G + lane;
        uint4 c0[4], c1[4];
        if (G >= 4) {
#pragma unroll
          for (int ch = 0; ch < 4; ch++) {
            const uint8_t* kc = smem + SM_KB + ch * KC_STRIDE * 2;
            const uint32_t a = *(const unsigned short*)(kc + (384 + n) * 2), bb = *(const unsigned short*)(kc + (385 + n) * 2);
            const uint32_t aa = a | (a << 16), b2 = bb | (bb << 16);
            const uint32_t tie = (n & 1) ? bb : a;
            c0[ch] = make_uint4(aa, a | (tie << 16), b2, b2);
            c1[ch] = make_uint4(aa, tie | (bb << 16), b2, b2);
          }
        } else if (G >= 2) {
#pragma unroll
          for (int ch = 0; ch < 4; ch++) {
            const uint8_t* kc = smem + SM_KB + ch * KC_STRIDE * 2;
            const uint32_t w0 = *(const uint32_t*)(kc + (256 + 2 * n) * 2), w1 = *(const uint32_t*)(kc + (258 + 2 * n) * 2);
            c0[ch] = make_uint4(dup_lo(w0), dup_hi(w0), __byte_perm(w0, w1, 0x5432), dup_lo(w1));
            c1[ch] = make_uint4(w0, dup_hi(w0), dup_lo(w1), dup_lo(w1));
          }
        } else if (G == 1) {
#pragma unroll
          for (int ch = 0; ch < 4; ch++) {
            const uint8_t* kc = smem + SM_KB + ch * KC_STRIDE * 2;
            const uint2 w01 = *(const uint2*)(kc + (128 + 4 * n) * 2);
            const uint32_t w2 = *(const uint32_t*)(kc + (132 + 4 * n) * 2);
            c0[ch] = make_uint4(w01.x, dup_lo(w01.y), w01.y, dup_lo(w2));
            c1[ch] = make_uint4(__byte_perm(w01.x, w01.y, 0x5432), dup_lo(w01.y), __byte_perm(w01.y, w2, 0x5432), dup_lo(w2));
          }
        } else {
#pragma unroll
          for (int ch = 0; ch < 4; ch++) {
            const uint8_t* kc = smem + SM_KB + ch * KC_STRIDE * 2;
            const uint4 wv = *(const uint4*)(kc + (8 * n) * 2);
            const uint32_t w4 = *(const uint32_t*)(kc + (8 * n + 8) * 2);
            c0[ch] = make_uint4(__byte_perm(wv.x, wv.y, 0x5432), __byte_perm(wv.y, wv.z, 0x5432), __byte_perm(wv.z, wv.w, 0x5432), __byte_perm(wv.w, w4, 0x5432));
            c1[ch] = make_uint4(wv.y, wv.z, wv.w, (n == 31) ? dup_lo(w4) : w4);
          }
          if (lane < 8) {
            const int ch = lane >> 1, hi = lane & 1;
            const uint32_t k01 = *(const uint32_t*)(smem + SM_KB + ch * KC_STRIDE * 2);
            uint8_t* e = smem + SM_X + CV_E + ch * E_CH + hi * 16;
            *(uint4*)e = make_uint4(0, 0, 0, hi ? (k01 << 16) : 0u);
            *(uint4*)(e + E_COPY) = make_uint4(0, 0, 0, hi ? k01 : 0u);
          }
        }
#pragma unroll
        for (int ch = 0; ch < 4; ch++) {
          uint8_t* e = smem + SM_X + CV_E + ch * E_CH + (n + 2) * 16;
          *(uint4*)e = c0[ch];
          *(uint4*)(e + E_COPY) = c1[ch];
        }
      }
        fence_async();
        __syncwarp();
        if (lane == 0) mbar_arrive(bars + 8 * B_RRDY);
      }
      if (lane == 0) {
        const uint32_t tag = ld_epoch() + 1;
        auto publish = [&](int s) {
          asm volatile("fence.proxy.async.global;" ::: "memory");
          st_release(g_flag + ((it_ * 8 + ((jf + 1 + s) & 7)) * 8 + jf), tag);
        };
#pragma unroll 1
        for (int s = w; s < 7; s += 2) {
          {
            part_store(s);
            asm volatile("cp.async.bulk.wait_group.read 0;" ::: "memory");
            mbar_arrive(bars + 8 * (B_STF + s));
          }
          if (s >= 2 && s < 6) {
            asm volatile("cp.async.bulk.wait_group 1;" ::: "memory");
            publish(s - 2);
          }
          if (s >= 4) {
            asm volatile("cp.async.bulk.wait_group 0;" ::: "memory");
            publish(s);
          }
        }
      }
      __syncwarp();
    }
    bar_sync(2, 128);
    if (tid == 256) {
      const uint32_t tk = atomicAdd(&g_exit, 1u);
      if (tk == NCTA - 1) {
        g_exit = 0;
        *(volatile uint32_t*)&g_epoch = ld_epoch() + 1;
      }
    }
  } else {
    asm volatile("setmaxnreg.inc.sync.aligned.u32 200;");
    const int wg = warp >> 2;
    const int g = lane >> 2, q = lane & 3;
    const uint32_t dsk = *(const uint32_t*)(P.D_skip + d0 + 2 * wg);
    uint32_t hf[56];
    {
      float acc[128];
#pragma unroll
      for (int i = 0; i < 128; i++) zero_reg(acc[i]);
#pragma unroll 1
      for (int st = 0; st < 16; st++) {
        const int slot = st % 5;
        if ((st & 1) == 0) mbar_wait(bars + 8 * (B_XFULL + (st >> 1)), 0);
        mbar_wait(bars + 8 * (B_FULL + slot), (st / 5) & 1);
        const uint64_t da = mkdesc(sb + SM_X + (st >> 1) * 16384 + wg * 8192 + (st & 1) * 64, 16, 1024, 1);
        const uint64_t db = mkdesc(sb + SM_RING + slot * 16384, 4096, 1024, 1);
        wg_fence();
        wgmma_ss_n256(acc, da, db);
        wgmma_ss_n256(acc, da + 2, db + 128);
        wg_commit();
        if (st > 0) {
          wg_wait<1>();
          if (lane == 0) mbar_arrive(bars + 8 * (B_EMPTY + (st - 1) % 5));
        }
      }
      wg_wait<0>();
      if (lane == 0) mbar_arrive(bars + 8 * (B_EMPTY + 15 % 5));
#pragma unroll
      for (int m = 0; m < 16; m++) {
        hf[2 * m] = hmul2_bf16(pack_bf16(acc[4 * m], acc[4 * m + 1]), pack_bf16(acc[64 + 4 * m], acc[64 + 4 * m + 1]));
        hf[2 * m + 1] = hmul2_bf16(pack_bf16(acc[4 * m + 2], acc[4 * m + 3]), pack_bf16(acc[64 + 4 * m + 2], acc[64 + 4 * m + 3]));
      }
    }
    float accA[32], accB[32];
    auto issue_half = [&](float (&acc)[32], int s, auto half_tag) {
      constexpr int half = decltype(half_tag)::value;
      if (half == 0) {
#pragma unroll
        for (int i = 0; i < 32; i++) zero_reg(acc[i]);
      }
      const int st = 32 + 2 * s + half;
      const int slot = st % 5;
      mbar_wait(bars + 8 * (B_FULL + slot), (st / 5) & 1);
      uint32_t sbase;
      asm volatile("mov.b32 %0, %1;" : "=r"(sbase) : "r"(sb + SM_RING + slot * 16384));
      const uint64_t db = mkdesc(sbase, 1024, 1024, 1);
      wg_fence();
#pragma unroll
      for (int k = 0; k < 7; k++) {
        const int ks = 7 * half + k;
        wgmma_rs_n64t(acc, hf[4 * ks], hf[4 * ks + 1], hf[4 * ks + 2], hf[4 * ks + 3], db + k * 128);
      }
      wg_commit();
    };
    auto release = [&](int st) { if (lane == 0) mbar_arrive(bars + 8 * (B_EMPTY + st % 5)); };
    using H0 = IC<0>;
    using H1 = IC<1>;
    {
      float accg[48], accu[48];
#pragma unroll
      for (int i = 0; i < 48; i++) { zero_reg(accg[i]); zero_reg(accu[i]); }
      const uint32_t xrow = sb + SM_X + (wg * 64 + (warp & 3) * 16 + (lane & 15)) * 128;
      const uint32_t xsw = lane & 7, xhi = lane >> 4;
      uint32_t a0[4], a1[4], a2[4], a3[4];
#pragma unroll 1
      for (int kb = 0; kb < 8; kb++) {
        const uint32_t xb = xrow + kb * 16384;
        {
          const int st = 16 + 2 * kb, slot = st % 5;
          ldsm4(a0, xb + (((0 + xhi) ^ xsw) << 4));
          ldsm4(a1, xb + (((2 + xhi) ^ xsw) << 4));
          mbar_wait(bars + 8 * (B_FULL + slot), (st / 5) & 1);
          const uint64_t db = mkdesc(sb + SM_RING + slot * 16384, 4096, 1024, 1);
          wg_fence();
          wgmma_rs_n96(accg, a0[0], a0[1], a0[2], a0[3], db);
          wgmma_rs_n96(accu, a0[0], a0[1], a0[2], a0[3], db + 512);
          wgmma_rs_n96(accg, a1[0], a1[1], a1[2], a1[3], db + 128);
          wgmma_rs_n96(accu, a1[0], a1[1], a1[2], a1[3], db + 128 + 512);
          wg_commit();
          wg_wait<1>();
          if (kb > 0 && lane == 0) mbar_arrive(bars + 8 * (B_EMPTY + (st - 1) % 5));
        }
        {
          const int st = 17 + 2 * kb, slot = st % 5;
          ldsm4(a2, xb + (((4 + xhi) ^ xsw) << 4));
          ldsm4(a3, xb + (((6 + xhi) ^ xsw) << 4));
          mbar_wait(bars + 8 * (B_FULL + slot), (st / 5) & 1);
          const uint64_t db = mkdesc(sb + SM_RING + slot * 16384, 4096, 1024, 1);
          wg_fence();
          wgmma_rs_n96(accg, a2[0], a2[1], a2[2], a2[3], db);
          wgmma_rs_n96(accu, a2[0], a2[1], a2[2], a2[3], db + 512);
          wgmma_rs_n96(accg, a3[0], a3[1], a3[2], a3[3], db + 128);
          wgmma_rs_n96(accu, a3[0], a3[1], a3[2], a3[3], db + 128 + 512);
          wg_commit();
          wg_wait<1>();
          if (lane == 0) {
            mbar_arrive(bars + 8 * (B_EMPTY + (st - 1) % 5));
            if (kb == 3) mbar_arrive(bars + 8 * (B_XFREE + 3));
          }
        }
      }
      issue_half(accA, 0, H0{});
      wg_wait<1>();
      if (lane == 0) { mbar_arrive(bars + 8 * (B_EMPTY + 31 % 5)); mbar_arrive(bars + 8 * (B_XFREE + 7)); }
#pragma unroll
      for (int m = 0; m < 12; m++) {
        hf[32 + 2 * m] = hmul2_bf16(pack_bf16(accg[4 * m], accg[4 * m + 1]), pack_bf16(accu[4 * m], accu[4 * m + 1]));
        hf[32 + 2 * m + 1] = hmul2_bf16(pack_bf16(accg[4 * m + 2], accg[4 * m + 3]), pack_bf16(accu[4 * m + 2], accu[4 * m + 3]));
      }
    }
    auto send_pass = [&](float (&acc)[32], int s) {
      uint4* dst = (uint4*)(smem + SM_X + part_slot(s, wg) + (warp & 3) * 2048) + lane;
#pragma unroll
      for (int c = 0; c < 4; c++) {
        uint4 v;
        v.x = pack_bf16(acc[8 * c], acc[8 * c + 1]); v.y = pack_bf16(acc[8 * c + 2], acc[8 * c + 3]);
        v.z = pack_bf16(acc[8 * c + 4], acc[8 * c + 5]); v.w = pack_bf16(acc[8 * c + 6], acc[8 * c + 7]);
        dst[c * 32] = v;
      }
    };
    auto send_signal = [&](int s) {
      fence_async();
      __syncwarp();
      if (lane == 0) mbar_arrive(bars + 8 * (B_SENT + s));
    };
    auto part_load = [&](uint4 (&v)[4], int k) {
      const uint4* sp = g_part + (size_t)(((it_ * 8 + jf) * 8 + ((jf - k) & 7)) * 8 + warp) * 128 + lane;
#pragma unroll
      for (int c = 0; c < 4; c++) v[c] = ld_cg4(sp + c * 32);
    };
    auto part_add = [&](const uint4 (&v)[4]) {
#pragma unroll
      for (int c = 0; c < 4; c++) {
        accA[8 * c] += bf_lo(v[c].x); accA[8 * c + 1] += bf_hi(v[c].x); accA[8 * c + 2] += bf_lo(v[c].y); accA[8 * c + 3] += bf_hi(v[c].y);
        accA[8 * c + 4] += bf_lo(v[c].z); accA[8 * c + 5] += bf_hi(v[c].z); accA[8 * c + 6] += bf_lo(v[c].w); accA[8 * c + 7] += bf_hi(v[c].w);
      }
    };
    issue_half(accA, 0, H1{}); wg_wait<1>(); release(32);
    mbar_wait(bars + 8 * (B_XFREE + 7), 0);
    issue_half(accB, 1, H0{}); wg_wait<1>(); release(33); send_pass(accA, 0);
    issue_half(accB, 1, H1{}); send_signal(0); wg_wait<1>(); release(34);
    issue_half(accA, 2, H0{}); wg_wait<1>(); release(35); send_pass(accB, 1);
    issue_half(accA, 2, H1{}); send_signal(1); wg_wait<1>(); release(36);
    issue_half(accB, 3, H0{}); wg_wait<1>(); release(37); send_pass(accA, 2);
    issue_half(accB, 3, H1{}); send_signal(2); wg_wait<1>(); release(38);
    issue_half(accA, 4, H0{}); wg_wait<1>(); release(39); send_pass(accB, 3);
    issue_half(accA, 4, H1{}); send_signal(3); wg_wait<1>(); release(40);
    issue_half(accB, 5, H0{}); wg_wait<1>(); release(41); mbar_wait(bars + 8 * (B_STF + 0), 0); send_pass(accA, 4);
    issue_half(accB, 5, H1{}); send_signal(4); wg_wait<1>(); release(42);
    wg_wait<0>(); send_pass(accB, 5);
    {
      const int w = warp & 3;
      mbar_wait(bars + 8 * B_RRDY, 0);
      const uint32_t zero = lds32(sb + SM_X + CV_R + (2 * wg + 1) * R_CH + 128 * 16);
      const int c = tid & 127;
      const float* Sr = (const float*)(smem + SM_X + CV_S + wg * S_WG) + (127 - c);
      float* Sw = (float*)(smem + SM_X + CV_S + wg * S_WG) + w * 16 * S_PITCH + g * S_PITCH + 2 * q;
      uint32_t fa[4][4], fb[4][4];
      uint32_t ares[8] = {0, 0, 0, 0, 0, 0, 0, 0}, rv[8];
      auto load_u = [&](int ch) {
        const uint4 r0v = *(const uint4*)(smem + SM_X + CV_R + ch * R_CH + (127 - c) * 16);
        const uint4 r1v = *(const uint4*)(smem + SM_X + CV_R + ch * R_CH + R_HALF + (127 - c) * 16);
        rv[0] = r0v.x; rv[1] = r0v.y; rv[2] = r0v.z; rv[3] = r0v.w; rv[4] = r1v.x; rv[5] = r1v.y; rv[6] = r1v.z; rv[7] = r1v.w;
      };
#define POST(r2, dk2)                                                                              \
      {                                                                                            \
        float y_[2];                                                                               \
        _Pragma("unroll") for (int t2 = 0; t2 < 2; t2++) {                                         \
          const int r0 = 2 * (r2) + t2;                                                            \
          const float s1 = c >= 1 ? Sr[(16 + r0) * S_PITCH + 1] : 0.f;                             \
          const float s2 = c >= 2 ? Sr[(32 + r0) * S_PITCH + 2] : 0.f;                             \
          const float s3 = c >= 3 ? Sr[(48 + r0) * S_PITCH + 3] : 0.f;                             \
          y_[t2] = (Sr[r0 * S_PITCH] + s1) + (s2 + s3);                                            \
        }                                                                                          \
        ares[r2] = hadd2_bf16(pack_bf16(y_[0], y_[1]), hmul2_bf16(__byte_perm(rv[7 - (r2)], rv[7 - (r2)], 0x1032), dk2)); \
      }
      auto store_a = [&](int ch) {
        uint4* ap = (uint4*)(smem + SM_X + CV_R + ch * R_CH + c * 32);
        ap[0] = make_uint4(ares[0], ares[1], ares[2], ares[3]);
        ap[1] = make_uint4(ares[4], ares[5], ares[6], ares[7]);
        fence_async();
      };
      const uint32_t eoff = ((g & 1) ? E_COPY : 0) + (16 * w + (g & ~1) + 2 * q) * 2;
      const uint32_t dkA = dup_lo(dsk), dkB = dup_hi(dsk);
      {
        const int ch = 2 * wg;
        const uint32_t ebase = sb + SM_X + CV_E + ch * E_CH + eoff;
        const uint64_t de = mkdesc(sb + SM_X + CV_R + ch * R_CH, R_HALF, 128, 0);
        conv_load4<0>(fa, ebase, zero);
        conv_load4<4>(fb, ebase, zero);
        CONV_CHANNEL(mbar_wait(bars + 8 * (B_STF + 1), 0); mbar_wait(bars + 8 * (B_STF + 2), 0); mbar_wait(bars + 8 * (B_STF + 3), 0); mbar_wait(bars + 8 * (B_STF + 4), 0);, send_signal(5);, )
      }
      issue_half(accA, 6, H0{});
      issue_half(accA, 6, H1{});
      bar_sync(6 + wg, 128);
      POST(0, dkA) POST(1, dkA) POST(2, dkA) POST(3, dkA) POST(4, dkA) POST(5, dkA) POST(6, dkA) POST(7, dkA)
      store_a(2 * wg);
      __syncwarp();
      if (lane == 0) mbar_arrive(bars + 8 * B_ADONE);
      {
        const int ch = 2 * wg + 1;
        const uint32_t ebase = sb + SM_X + CV_E + ch * E_CH + eoff;
        const uint64_t de = mkdesc(sb + SM_X + CV_R + ch * R_CH, R_HALF, 128, 0);
        conv_load4<0>(fa, ebase, zero);
        conv_load4<4>(fb, ebase, zero);
        wg_wait<0>();
        send_pass(accA, 6);
        CONV_CHANNEL(bar_sync(6 + wg, 128);, send_signal(6);, )
        bar_sync(6 + wg, 128);
        POST(0, dkB) POST(1, dkB) POST(2, dkB) POST(3, dkB) POST(4, dkB) POST(5, dkB) POST(6, dkB) POST(7, dkB)
        store_a(ch);
        __syncwarp();
        if (lane == 0) mbar_arrive(bars + 8 * (B_ADONE + 1));
      }
#undef POST
    }
    {
      uint4 v0[4], v1[4], v2[4], v3[4];
      mbar_wait(bars + 8 * B_GOT, 0);
      part_load(v0, 1);
      part_load(v1, 2);
      part_load(v2, 3);
      part_load(v3, 4);
      issue_half(accB, 7, H0{});
      issue_half(accB, 7, H1{});
#pragma unroll
      for (int i = 0; i < 32; i++) accA[i] = 0.f;
      part_add(v0); part_load(v0, 5);
      part_add(v1); part_load(v1, 6);
      part_add(v2); part_load(v2, 7);
      part_add(v3);
      part_add(v0);
      part_add(v1);
      part_add(v2);
    }
    mbar_wait(bars + 8 * B_ATILE, 0);
    const int row0 = it_ * 128 + warp * 16 + g;
    const float g0 = __uint_as_float(ld_cg1(g_gate + row0)), g1 = __uint_as_float(ld_cg1(g_gate + row0 + 8));
    uint32_t av[16];
    {
      const int dl = (lane & 7) + ((lane >> 4) << 3);
      const int chunk = 2 * (warp & 3) + ((lane >> 3) & 1);
      const uint32_t abase = sb + SM_AT + wg * 8192 + dl * 128 + ((chunk ^ (lane & 7)) << 4);
#pragma unroll
      for (int m2 = 0; m2 < 4; m2++) {
        asm volatile("ldmatrix.sync.aligned.m8n8.x4.trans.shared.b16 {%0,%1,%2,%3}, [%4];"
                     : "=r"(av[4 * m2]), "=r"(av[4 * m2 + 1]), "=r"(av[4 * m2 + 2]), "=r"(av[4 * m2 + 3]) : "r"(abase + m2 * 2048) : "memory");
      }
    }
    wg_wait<0>();
    const uint32_t gg0 = pack_bf16(g0, g0), gg1 = pack_bf16(g1, g1);
    const uint32_t og0 = pack_bf16(1.f - g0, 1.f - g0), og1 = pack_bf16(1.f - g1, 1.f - g1);
    uint32_t ov[16];
#pragma unroll
    for (int m = 0; m < 8; m++) {
      const uint32_t b0 = pack_bf16(accA[4 * m] + accB[4 * m], accA[4 * m + 1] + accB[4 * m + 1]);
      const uint32_t b1 = pack_bf16(accA[4 * m + 2] + accB[4 * m + 2], accA[4 * m + 3] + accB[4 * m + 3]);
      ov[2 * m] = hadd2_bf16(hmul2_bf16(gg0, av[2 * m]), hmul2_bf16(og0, b0));
      ov[2 * m + 1] = hadd2_bf16(hmul2_bf16(gg1, av[2 * m + 1]), hmul2_bf16(og1, b1));
    }
    {
      const uint32_t ob = sb + SM_X + CV_S + wg * S_WG + (warp & 3) * 2048;
      const int srow = (lane & 7) + ((lane >> 3) & 1) * 8;
#pragma unroll
      for (int m2 = 0; m2 < 4; m2++) {
        const int chunk = 2 * m2 + (lane >> 4);
        asm volatile("stmatrix.sync.aligned.m8n8.x4.shared.b16 [%0], {%1,%2,%3,%4};"
                     ::"r"(ob + srow * 128 + ((chunk ^ (srow & 7)) << 4)), "r"(ov[4 * m2]), "r"(ov[4 * m2 + 1]), "r"(ov[4 * m2 + 2]), "r"(ov[4 * m2 + 3]) : "memory");
      }
      __syncwarp();
#pragma unroll
      for (int i = 0; i < 4; i++) {
        const int r = 4 * i + (lane >> 3), chunk = lane & 7;
        const uint4 v = *(const uint4*)(smem + SM_X + CV_S + wg * S_WG + (warp & 3) * 2048 + r * 128 + ((chunk ^ (r & 7)) << 4));
        *(uint4*)(P.out + (it_ * 128 + warp * 16 + r) * D_ + jf * 64 + chunk * 8) = v;
      }
    }
  }
}

typedef CUresult (*EncFn)(CUtensorMap*, CUtensorMapDataType, cuuint32_t, void*, const cuuint64_t*, const cuuint64_t*, const cuuint32_t*,
                          const cuuint32_t*, CUtensorMapInterleave, CUtensorMapSwizzle, CUtensorMapL2promotion, CUtensorMapFloatOOBfill);

struct HostState {
  bool ready;
  const void* key[4];
  Maps M;
};
HostState hs;

}

extern "C" void kernel_launch(void* const* d_in, const int* in_sizes, int n_in, void* d_out, int out_size) {
  (void)in_sizes; (void)n_in; (void)out_size;
  void* x = d_in[0];
  void* wg = d_in[8];
  void* wu = d_in[9];
  void* wd = d_in[10];
  if (!hs.ready || hs.key[0] != x || hs.key[1] != wg || hs.key[2] != wu || hs.key[3] != wd) {
    void* fn = nullptr;
    cudaDriverEntryPointQueryResult qr;
    cudaGetDriverEntryPoint("cuTensorMapEncodeTiled", &fn, cudaEnableDefault, &qr);
    EncFn enc = (EncFn)fn;
    const cuuint32_t es[3] = {1, 1, 1};
    const CUtensorMapDataType BF = CU_TENSOR_MAP_DATA_TYPE_BFLOAT16;
    const CUtensorMapInterleave IN = CU_TENSOR_MAP_INTERLEAVE_NONE;
    const CUtensorMapL2promotion PR = CU_TENSOR_MAP_L2_PROMOTION_L2_128B;
    const CUtensorMapFloatOOBfill OO = CU_TENSOR_MAP_FLOAT_OOB_FILL_NONE;
    {
      cuuint64_t gd[2] = {(cuuint64_t)D_, (cuuint64_t)L_}; cuuint64_t gs[1] = {(cuuint64_t)D_ * 2}; cuuint32_t box[2] = {64, 128};
      enc(&hs.M.X, BF, 2, x, gd, gs, box, es, IN, CU_TENSOR_MAP_SWIZZLE_128B, PR, OO);
    }
    {
      cuuint64_t gd[2] = {(cuuint64_t)F_, (cuuint64_t)D_}; cuuint64_t gs[1] = {(cuuint64_t)F_ * 2}; cuuint32_t box[2] = {64, 32};
      enc(&hs.M.Wg, BF, 2, wg, gd, gs, box, es, IN, CU_TENSOR_MAP_SWIZZLE_128B, PR, OO);
      enc(&hs.M.Wu, BF, 2, wu, gd, gs, box, es, IN, CU_TENSOR_MAP_SWIZZLE_128B, PR, OO);
      for (int o = 0; o < 2; o++) {
        cuuint64_t gd3[3] = {64, (cuuint64_t)D_, (cuuint64_t)(F_ / 64 - o)}; cuuint64_t gs3[2] = {(cuuint64_t)F_ * 2, 128};
        cuuint32_t box3[3] = {64, 32, 2};
        enc(&hs.M.Wg3[o], BF, 3, (char*)wg + 64 * o, gd3, gs3, box3, es, IN, CU_TENSOR_MAP_SWIZZLE_128B, PR, OO);
        enc(&hs.M.Wu3[o], BF, 3, (char*)wu + 64 * o, gd3, gs3, box3, es, IN, CU_TENSOR_MAP_SWIZZLE_128B, PR, OO);
      }
    }
    {
      cuuint64_t gd[2] = {(cuuint64_t)D_, (cuuint64_t)F_}; cuuint64_t gs[1] = {(cuuint64_t)D_ * 2}; cuuint32_t box[2] = {64, 112};
      enc(&hs.M.Wd, BF, 2, wd, gd, gs, box, es, IN, CU_TENSOR_MAP_SWIZZLE_128B, PR, OO);
    }
    {
      void* pa = nullptr;
      cudaGetSymbolAddress(&pa, g_aT);
      cuuint64_t gd[2] = {(cuuint64_t)L_, (cuuint64_t)D_}; cuuint64_t gs[1] = {(cuuint64_t)L_ * 2}; cuuint32_t box[2] = {64, 64};
      enc(&hs.M.AT, BF, 2, pa, gd, gs, box, es, IN, CU_TENSOR_MAP_SWIZZLE_128B, PR, OO);
    }
    cudaFuncSetAttribute(fused_kernel, cudaFuncAttributeMaxDynamicSharedMemorySize, SM_TOTAL);
    hs.key[0] = x; hs.key[1] = wg; hs.key[2] = wu; hs.key[3] = wd;
    hs.ready = true;
  }
  Params P;
  P.x = (const __nv_bfloat16*)d_in[0];
  P.log_A_real = (const __nv_bfloat16*)d_in[1];
  P.A_imag = (const __nv_bfloat16*)d_in[2];
  P.C_real = (const __nv_bfloat16*)d_in[3];
  P.C_imag = (const __nv_bfloat16*)d_in[4];
  P.log_dt = (const __nv_bfloat16*)d_in[5];
  P.D_skip = (const __nv_bfloat16*)d_in[6];
  P.gate_w = (const __nv_bfloat16*)d_in[11];
  P.w_gate = (const __nv_bfloat16*)wg;
  P.w_up = (const __nv_bfloat16*)wu;
  P.w_down = (const __nv_bfloat16*)wd;
  P.out = (__nv_bfloat16*)d_out;
  fused_kernel<<<NCTA, NTHREADS, SM_TOTAL>>>(hs.M, P);
}
```
